```python
import torch

def _softmax(x, axis=-1):
    return torch.softmax(x, dim=axis)
def _gelu(x):
    return torch.nn.functional.gelu(x, approximate="tanh")
def _silu(x):
    return torch.nn.functional.silu(x)
def _sigmoid(x):
    return torch.sigmoid(x)
def _layernorm(x, axis=-1, eps=1e-5):
    m = x.mean(dim=axis, keepdim=True)
    v = x.var(dim=axis, keepdim=True, unbiased=False)
    return (x - m) / torch.sqrt(v + eps)
def _scatter_add(tgt, idx, src, axis=0):
    return tgt.clone().index_add_(axis, idx, src)
def _segment_sum(src, seg, n):
    out = torch.zeros((n,) + src.shape[1:], dtype=src.dtype)
    return out.index_add_(0, seg, src)
def _pad(x, pw):
    flat = tuple(v for pair in reversed(pw) for v in pair)
    return torch.nn.functional.pad(x, flat)

kernel_name = 'standalone__weight_only_int_squeezellm__prompt'

def setup_inputs():

    _w = (lambda a: (lambda t: t.to(torch.bfloat16) if t.is_floating_point() else t)(torch.as_tensor(a)))
    B, S, D, F = 1, 2048, 1024, 3584
    bits = 8 if (2 <= 8 <= 4) else 4
    L = 2 ** bits
    qw = torch.randint(0, L, (D, F)).to(torch.int64)
    lut = (lambda *s: torch.randn(*s, dtype=torch.bfloat16) * 0.05)(L, F)
    return {
        "x": _w((lambda *s: torch.randn(*s, dtype=torch.bfloat16) * 0.05)(B, S, D)),
        "qw": _w(qw),
        "lut": _w(lut),
    }

def reference(x, qw, lut):
    w = (lambda x, i, axis: torch.take_along_dim(x, i, dim=axis))(lut, qw, axis=0)
    w = (lambda x, dt: x.to(dt))(w, x.dtype)
    return torch.einsum('bsd,df->bsf', x, w)
```

```cpp
#include <cuda_runtime.h>
#include <cuda_bf16.h>
#include <cuda.h>
#include <stdint.h>
#include <cstdio>
#include <algorithm>

namespace {

constexpr int M_ = 2048, K_ = 1024, N_ = 3584;
constexpr int BF = 128, BK = 64;
constexpr int TA = 256, TB = 192;
#define TCC 232
constexpr int TC = TCC, TD = 184;
constexpr int STAGES = 4;
constexpr int KBLKS = K_ / BK;
constexpr int X_BYTES = TA * BK * 2;
constexpr int UNIT_BYTES = BK * 32 * 4;
constexpr int SLAB_BYTES = BF * BK;
constexpr int STAGE_BYTES = X_BYTES + SLAB_BYTES;
constexpr int OFF_STG = STAGES * STAGE_BYTES;
constexpr int OFF_PL = OFF_STG + 3 * UNIT_BYTES;
constexpr int OFF_TAB = OFF_PL + 2048;
constexpr int OFF_BAR = OFF_STG + 65536;
constexpr int W_OFF = 16 * KBLKS * SLAB_BYTES;
constexpr int SMEM_BYTES = OFF_BAR + 512;
constexpr int NUM_CTAS = 132;
constexpr int NTHREADS = 384;
constexpr int NPACK = 3;
#define XT1 1200
#define XT2 2000
#define XT3 2900
#define WT0 1800
#define WTS 1000
#define WT1 3100
#define TE 1900
#define TE2 900
#define WT2 3800
#define NWG 5
#define S1D 400
#define TP 2300
#define PC 900
#define PC0 0
#define OB 32
#define PACE 300
#define WAITS 7
#define D0 600
#define PER 1200
#define PER2 900
#define R1 7
#define WB 3
#define NOLK 0
#define SPC 0
#define LT0 7500
#define LTS 18
#define X3 1
#define XPROM CU_TENSOR_MAP_L2_PROMOTION_L2_128B
#define QPROM CU_TENSOR_MAP_L2_PROMOTION_L2_128B
#define SLS 1
#define SK 3
#define S1 1
#define NSP 1
#define NSI 10
#define S1W 1
#define S1B 1
#define FT0 3000
#define FTS 100
#define TEXP 0
#define CUNR 1
#define NL 384
#define SKW 1
#define LZ 1
#define XI0 3
#define XI1 7
#define WI 5
#define WROWS 128
#define FL 0
#define XROWS 96
#define NOST 0
#define HLP 0
#define N88 1
#define ACQ 1
constexpr int CUN = CUNR;
static_assert(SMEM_BYTES <= 232448, "smem");
static_assert(TB * 128 + 2 * SLAB_BYTES == STAGE_BYTES, "stage");
constexpr int B_FULL = 0, B_EMPTY = STAGES, B_SLOT = 2 * STAGES, B_PACKED = B_SLOT + NPACK, B_STORED = B_PACKED + 1,
              B_EPOCH = B_STORED + 1, B_RDY = B_EPOCH + 1, B_STG = B_RDY + 2, B_PL = B_STG + 2;
constexpr int NBARS = B_PL + 1;
constexpr int OFF_EPOCH = OFF_BAR + 8 * NBARS;
constexpr int B_FARM = 32;

__device__ __align__(1024) uint8_t g_p[W_OFF + 12 * KBLKS * 2 * SLAB_BYTES];
__device__ __align__(128) unsigned int g_count[32 * 97];

__device__ __forceinline__ uint32_t smem_u32(const void* p) { return (uint32_t)__cvta_generic_to_shared(p); }
__device__ __forceinline__ void mbar_init(uint32_t bar, uint32_t cnt) {
  asm volatile("mbarrier.init.shared::cta.b64 [%0], %1;" ::"r"(bar), "r"(cnt) : "memory");
}
__device__ __forceinline__ void mbar_expect_tx(uint32_t bar, uint32_t bytes) {
  asm volatile("mbarrier.arrive.expect_tx.shared::cta.b64 _, [%0], %1;" ::"r"(bar), "r"(bytes) : "memory");
}
__device__ __forceinline__ bool mbar_try_wait(uint32_t bar, uint32_t parity) {
  uint32_t ok;
  asm volatile(
      "{\n.reg .pred p;\n"
      "mbarrier.try_wait.parity.shared::cta.b64 p, [%1], %2;\n"
      "selp.u32 %0, 1, 0, p;\n}\n"
      : "=r"(ok) : "r"(bar), "r"(parity) : "memory");
  return ok != 0;
}
__device__ __forceinline__ bool mbar_test_wait(uint32_t bar, uint32_t parity) {
  uint32_t ok;
  asm volatile(
      "{\n.reg .pred p;\n"
      "mbarrier.test_wait.parity.shared::cta.b64 p, [%1], %2;\n"
      "selp.u32 %0, 1, 0, p;\n}\n"
      : "=r"(ok) : "r"(bar), "r"(parity) : "memory");
  return ok != 0;
}
__device__ __forceinline__ void mbar_wait(uint32_t bar, uint32_t parity) {
  asm volatile(
      "{\n.reg .pred p;\n.reg .u32 c;\n"
      "mbarrier.try_wait.parity.shared::cta.b64 p, [%0], %1;\n"
      "@p bra.uni DONE;\n"
      "mov.u32 c, 0;\n"
      "SPIN:\n"
      "mbarrier.try_wait.parity.shared::cta.b64 p, [%0], %1;\n"
      "add.u32 c, c, 1;\n"
      "setp.ge.or.u32 p, c, 0x100000, p;\n"
      "@!p bra.uni SPIN;\n"
      "DONE:\n}\n"
      ::"r"(bar), "r"(parity) : "memory");
}
__device__ __forceinline__ void mbar_arrive(uint32_t bar) {
  asm volatile("mbarrier.arrive.shared::cta.b64 _, [%0];" ::"r"(bar) : "memory");
}
__device__ __forceinline__ uint32_t mapa(uint32_t a, uint32_t cta) {
  uint32_t r;
  asm("mapa.shared::cluster.u32 %0, %1, %2;" : "=r"(r) : "r"(a), "r"(cta));
  return r;
}
__device__ __forceinline__ void mbar_arrive_remote_if(uint32_t ra, uint32_t cond) {
  asm volatile("{\n.reg .pred p;\nsetp.ne.u32 p, %1, 0;\n@p mbarrier.arrive.shared::cluster.b64 _, [%0];\n}\n" ::"r"(ra), "r"(cond) : "memory");
}
__device__ __forceinline__ void tma_load_2d(uint32_t dst, const CUtensorMap* map, uint32_t bar, int c0, int c1) {
  asm volatile(
      "cp.async.bulk.tensor.2d.shared::cluster.global.mbarrier::complete_tx::bytes [%0], [%1, {%3, %4}], [%2];"
      ::"r"(dst), "l"((uint64_t)map), "r"(bar), "r"(c0), "r"(c1) : "memory");
}
__device__ __forceinline__ void tma_load_2d_mc(uint32_t dst, const CUtensorMap* map, uint32_t bar, int c0, int c1, uint16_t mask) {
  asm volatile(
      "cp.async.bulk.tensor.2d.shared::cluster.global.mbarrier::complete_tx::bytes.multicast::cluster [%0], [%1, {%3, %4}], [%2], %5;"
      ::"r"(dst), "l"((uint64_t)map), "r"(bar), "r"(c0), "r"(c1), "h"(mask) : "memory");
}
__device__ __forceinline__ void tma_load_2d_mc_w(uint32_t dst, const CUtensorMap* map, uint32_t bar, int c0, int c1, uint32_t bytes) {
  asm volatile(
      "{\n.reg .pred p;\nelect.sync _|p, 0xffffffff;\n"
      "@p mbarrier.arrive.expect_tx.shared::cta.b64 _, [%2], %6;\n"
      "@p cp.async.bulk.tensor.2d.shared::cluster.global.mbarrier::complete_tx::bytes.multicast::cluster [%0], [%1, {%3, %4}], [%2], %5;\n}\n"
      ::"r"(dst), "l"((uint64_t)map), "r"(bar), "r"(c0), "r"(c1), "h"((uint16_t)3), "r"(bytes) : "memory");
}
__device__ __forceinline__ void bulk_load_w(uint32_t dst, const void* src, uint32_t bytes, uint32_t bar) {
  asm volatile("{\n.reg .pred p;\nelect.sync _|p, 0xffffffff;\n"
               "@p cp.async.bulk.shared::cluster.global.mbarrier::complete_tx::bytes [%0], [%1], %2, [%3];\n}\n"
               ::"r"(dst), "l"(src), "r"(bytes), "r"(bar) : "memory");
}
__device__ __forceinline__ void tma_load_2d_w(uint32_t dst, const CUtensorMap* map, uint32_t bar, int c0, int c1) {
  asm volatile(
      "{\n.reg .pred p;\nelect.sync _|p, 0xffffffff;\n"
      "@p cp.async.bulk.tensor.2d.shared::cluster.global.mbarrier::complete_tx::bytes [%0], [%1, {%3, %4}], [%2];\n}\n"
      ::"r"(dst), "l"((uint64_t)map), "r"(bar), "r"(c0), "r"(c1) : "memory");
}
__device__ __forceinline__ void tma_prefetch_2d(const CUtensorMap* map, int c0, int c1) {
  asm volatile("cp.async.bulk.prefetch.tensor.2d.L2.global [%0, {%1, %2}];" ::"l"((uint64_t)map), "r"(c0), "r"(c1) : "memory");
}
__device__ __forceinline__ void bulk_load(uint32_t dst, const void* src, uint32_t bytes, uint32_t bar) {
  asm volatile("cp.async.bulk.shared::cluster.global.mbarrier::complete_tx::bytes [%0], [%1], %2, [%3];"
               ::"r"(dst), "l"(src), "r"(bytes), "r"(bar) : "memory");
}
__device__ __forceinline__ void tma_store_2d(const CUtensorMap* map, uint32_t src, int c0, int c1) {
  asm volatile("cp.async.bulk.tensor.2d.global.shared::cta.bulk_group [%0, {%2, %3}], [%1];"
               ::"l"((uint64_t)map), "r"(src), "r"(c0), "r"(c1) : "memory");
}
__device__ __forceinline__ void bulk_commit() { asm volatile("cp.async.bulk.commit_group;" ::: "memory"); }
template <int N> __device__ __forceinline__ void bulk_wait_read() { asm volatile("cp.async.bulk.wait_group.read %0;" ::"n"(N) : "memory"); }
__device__ __forceinline__ void cluster_arrive_relaxed() { asm volatile("barrier.cluster.arrive.relaxed.aligned;" ::: "memory"); }
__device__ __forceinline__ void cluster_wait() { asm volatile("barrier.cluster.wait.acquire.aligned;" ::: "memory"); }
__device__ __forceinline__ void wgmma_fence() { asm volatile("wgmma.fence.sync.aligned;" ::: "memory"); }
__device__ __forceinline__ void wgmma_commit() { asm volatile("wgmma.commit_group.sync.aligned;" ::: "memory"); }
template <int N> __device__ __forceinline__ void wgmma_wait() { asm volatile("wgmma.wait_group.sync.aligned %0;" ::"n"(N) : "memory"); }
template <int N> __device__ __forceinline__ void fence_regs(float (&p)[N]) {
#pragma unroll
  for (int i = 0; i < N; i++) asm volatile("" : "+f"(p[i]) :: "memory");
}
__device__ __forceinline__ uint32_t make_desc(uint32_t addr) { return ((addr & 0x3FFFF) >> 4) | (1u << 16); }

template <int N> __device__ __forceinline__ void wgmma_rs(float* d, const uint32_t* a, uint32_t descB, uint32_t accum);
template <> __device__ __forceinline__ void wgmma_rs<192>(float* d, const uint32_t* a, uint32_t descB, uint32_t accum) {
  asm volatile(
    "{\n.reg .pred p;\n.reg .b64 db;\n"
    "setp.ne.b32 p, %101, 0;\n"
    "mov.b64 db, {%100, 0x40000040};\n"
    "wgmma.mma_async.sync.aligned.m64n192k16.f32.bf16.bf16 "
    "{%0, %1, %2, %3, %4, %5, %6, %7, %8, %9, %10, %11, %12, %13, %14, %15, %16, %17, %18, %19, %20, %21, %22, %23, %24, %25, %26, %27, %28, %29, %30, %31, %32, %33, %34, %35, %36, %37, %38, %39, %40, %41, %42, %43, %44, %45, %46, %47, %48, %49, %50, %51, %52, %53, %54, %55, %56, %57, %58, %59, %60, %61, %62, %63, %64, %65, %66, %67, %68, %69, %70, %71, %72, %73, %74, %75, %76, %77, %78, %79, %80, %81, %82, %83, %84, %85, %86, %87, %88, %89, %90, %91, %92, %93, %94, %95}, "
    "{%96, %97, %98, %99}, db, p, 1, 1, 0;\n"
    "}\n"
    : "+f"(d[0]), "+f"(d[1]), "+f"(d[2]), "+f"(d[3]), "+f"(d[4]), "+f"(d[5]), "+f"(d[6]), "+f"(d[7]), "+f"(d[8]), "+f"(d[9]), "+f"(d[10]), "+f"(d[11]), "+f"(d[12]), "+f"(d[13]), "+f"(d[14]), "+f"(d[15]), "+f"(d[16]), "+f"(d[17]), "+f"(d[18]), "+f"(d[19]), "+f"(d[20]), "+f"(d[21]), "+f"(d[22]), "+f"(d[23]), "+f"(d[24]), "+f"(d[25]), "+f"(d[26]), "+f"(d[27]), "+f"(d[28]), "+f"(d[29]), "+f"(d[30]), "+f"(d[31]), "+f"(d[32]), "+f"(d[33]), "+f"(d[34]), "+f"(d[35]), "+f"(d[36]), "+f"(d[37]), "+f"(d[38]), "+f"(d[39]), "+f"(d[40]), "+f"(d[41]), "+f"(d[42]), "+f"(d[43]), "+f"(d[44]), "+f"(d[45]), "+f"(d[46]), "+f"(d[47]), "+f"(d[48]), "+f"(d[49]), "+f"(d[50]), "+f"(d[51]), "+f"(d[52]), "+f"(d[53]), "+f"(d[54]), "+f"(d[55]), "+f"(d[56]), "+f"(d[57]), "+f"(d[58]), "+f"(d[59]), "+f"(d[60]), "+f"(d[61]), "+f"(d[62]), "+f"(d[63]), "+f"(d[64]), "+f"(d[65]), "+f"(d[66]), "+f"(d[67]), "+f"(d[68]), "+f"(d[69]), "+f"(d[70]), "+f"(d[71]), "+f"(d[72]), "+f"(d[73]), "+f"(d[74]), "+f"(d[75]), "+f"(d[76]), "+f"(d[77]), "+f"(d[78]), "+f"(d[79]), "+f"(d[80]), "+f"(d[81]), "+f"(d[82]), "+f"(d[83]), "+f"(d[84]), "+f"(d[85]), "+f"(d[86]), "+f"(d[87]), "+f"(d[88]), "+f"(d[89]), "+f"(d[90]), "+f"(d[91]), "+f"(d[92]), "+f"(d[93]), "+f"(d[94]), "+f"(d[95])
    : "r"(a[0]), "r"(a[1]), "r"(a[2]), "r"(a[3]), "r"(descB), "r"(accum));
}
template <> __device__ __forceinline__ void wgmma_rs<96>(float* d, const uint32_t* a, uint32_t descB, uint32_t accum) {
  asm volatile(
    "{\n.reg .pred p;\n.reg .b64 db;\n"
    "setp.ne.b32 p, %53, 0;\n"
    "mov.b64 db, {%52, 0x40000040};\n"
    "wgmma.mma_async.sync.aligned.m64n96k16.f32.bf16.bf16 "
    "{%0, %1, %2, %3, %4, %5, %6, %7, %8, %9, %10, %11, %12, %13, %14, %15, %16, %17, %18, %19, %20, %21, %22, %23, %24, %25, %26, %27, %28, %29, %30, %31, %32, %33, %34, %35, %36, %37, %38, %39, %40, %41, %42, %43, %44, %45, %46, %47}, "
    "{%48, %49, %50, %51}, db, p, 1, 1, 0;\n"
    "}\n"
    : "+f"(d[0]), "+f"(d[1]), "+f"(d[2]), "+f"(d[3]), "+f"(d[4]), "+f"(d[5]), "+f"(d[6]), "+f"(d[7]), "+f"(d[8]), "+f"(d[9]), "+f"(d[10]), "+f"(d[11]), "+f"(d[12]), "+f"(d[13]), "+f"(d[14]), "+f"(d[15]), "+f"(d[16]), "+f"(d[17]), "+f"(d[18]), "+f"(d[19]), "+f"(d[20]), "+f"(d[21]), "+f"(d[22]), "+f"(d[23]), "+f"(d[24]), "+f"(d[25]), "+f"(d[26]), "+f"(d[27]), "+f"(d[28]), "+f"(d[29]), "+f"(d[30]), "+f"(d[31]), "+f"(d[32]), "+f"(d[33]), "+f"(d[34]), "+f"(d[35]), "+f"(d[36]), "+f"(d[37]), "+f"(d[38]), "+f"(d[39]), "+f"(d[40]), "+f"(d[41]), "+f"(d[42]), "+f"(d[43]), "+f"(d[44]), "+f"(d[45]), "+f"(d[46]), "+f"(d[47])
    : "r"(a[0]), "r"(a[1]), "r"(a[2]), "r"(a[3]), "r"(descB), "r"(accum));
}
template <> __device__ __forceinline__ void wgmma_rs<88>(float* d, const uint32_t* a, uint32_t descB, uint32_t accum) {
  asm volatile(
    "{\n.reg .pred p;\n.reg .b64 db;\n"
    "setp.ne.b32 p, %49, 0;\n"
    "mov.b64 db, {%48, 0x40000040};\n"
    "wgmma.mma_async.sync.aligned.m64n88k16.f32.bf16.bf16 "
    "{%0, %1, %2, %3, %4, %5, %6, %7, %8, %9, %10, %11, %12, %13, %14, %15, %16, %17, %18, %19, %20, %21, %22, %23, %24, %25, %26, %27, %28, %29, %30, %31, %32, %33, %34, %35, %36, %37, %38, %39, %40, %41, %42, %43}, "
    "{%44, %45, %46, %47}, db, p, 1, 1, 0;\n"
    "}\n"
    : "+f"(d[0]), "+f"(d[1]), "+f"(d[2]), "+f"(d[3]), "+f"(d[4]), "+f"(d[5]), "+f"(d[6]), "+f"(d[7]), "+f"(d[8]), "+f"(d[9]), "+f"(d[10]), "+f"(d[11]), "+f"(d[12]), "+f"(d[13]), "+f"(d[14]), "+f"(d[15]), "+f"(d[16]), "+f"(d[17]), "+f"(d[18]), "+f"(d[19]), "+f"(d[20]), "+f"(d[21]), "+f"(d[22]), "+f"(d[23]), "+f"(d[24]), "+f"(d[25]), "+f"(d[26]), "+f"(d[27]), "+f"(d[28]), "+f"(d[29]), "+f"(d[30]), "+f"(d[31]), "+f"(d[32]), "+f"(d[33]), "+f"(d[34]), "+f"(d[35]), "+f"(d[36]), "+f"(d[37]), "+f"(d[38]), "+f"(d[39]), "+f"(d[40]), "+f"(d[41]), "+f"(d[42]), "+f"(d[43])
    : "r"(a[0]), "r"(a[1]), "r"(a[2]), "r"(a[3]), "r"(descB), "r"(accum));
}
template <> __device__ __forceinline__ void wgmma_rs<64>(float* d, const uint32_t* a, uint32_t descB, uint32_t accum) {
  asm volatile(
    "{\n.reg .pred p;\n.reg .b64 db;\n"
    "setp.ne.b32 p, %37, 0;\n"
    "mov.b64 db, {%36, 0x40000040};\n"
    "wgmma.mma_async.sync.aligned.m64n64k16.f32.bf16.bf16 "
    "{%0, %1, %2, %3, %4, %5, %6, %7, %8, %9, %10, %11, %12, %13, %14, %15, %16, %17, %18, %19, %20, %21, %22, %23, %24, %25, %26, %27, %28, %29, %30, %31}, "
    "{%32, %33, %34, %35}, db, p, 1, 1, 0;\n"
    "}\n"
    : "+f"(d[0]), "+f"(d[1]), "+f"(d[2]), "+f"(d[3]), "+f"(d[4]), "+f"(d[5]), "+f"(d[6]), "+f"(d[7]), "+f"(d[8]), "+f"(d[9]), "+f"(d[10]), "+f"(d[11]), "+f"(d[12]), "+f"(d[13]), "+f"(d[14]), "+f"(d[15]), "+f"(d[16]), "+f"(d[17]), "+f"(d[18]), "+f"(d[19]), "+f"(d[20]), "+f"(d[21]), "+f"(d[22]), "+f"(d[23]), "+f"(d[24]), "+f"(d[25]), "+f"(d[26]), "+f"(d[27]), "+f"(d[28]), "+f"(d[29]), "+f"(d[30]), "+f"(d[31])
    : "r"(a[0]), "r"(a[1]), "r"(a[2]), "r"(a[3]), "r"(descB), "r"(accum));
}
template <> __device__ __forceinline__ void wgmma_rs<56>(float* d, const uint32_t* a, uint32_t descB, uint32_t accum) {
  asm volatile(
    "{\n.reg .pred p;\n.reg .b64 db;\n"
    "setp.ne.b32 p, %33, 0;\n"
    "mov.b64 db, {%32, 0x40000040};\n"
    "wgmma.mma_async.sync.aligned.m64n56k16.f32.bf16.bf16 "
    "{%0, %1, %2, %3, %4, %5, %6, %7, %8, %9, %10, %11, %12, %13, %14, %15, %16, %17, %18, %19, %20, %21, %22, %23, %24, %25, %26, %27}, "
    "{%28, %29, %30, %31}, db, p, 1, 1, 0;\n"
    "}\n"
    : "+f"(d[0]), "+f"(d[1]), "+f"(d[2]), "+f"(d[3]), "+f"(d[4]), "+f"(d[5]), "+f"(d[6]), "+f"(d[7]), "+f"(d[8]), "+f"(d[9]), "+f"(d[10]), "+f"(d[11]), "+f"(d[12]), "+f"(d[13]), "+f"(d[14]), "+f"(d[15]), "+f"(d[16]), "+f"(d[17]), "+f"(d[18]), "+f"(d[19]), "+f"(d[20]), "+f"(d[21]), "+f"(d[22]), "+f"(d[23]), "+f"(d[24]), "+f"(d[25]), "+f"(d[26]), "+f"(d[27])
    : "r"(a[0]), "r"(a[1]), "r"(a[2]), "r"(a[3]), "r"(descB), "r"(accum));
}
template <> __device__ __forceinline__ void wgmma_rs<48>(float* d, const uint32_t* a, uint32_t descB, uint32_t accum) {
  asm volatile(
    "{\n.reg .pred p;\n.reg .b64 db;\n"
    "setp.ne.b32 p, %29, 0;\n"
    "mov.b64 db, {%28, 0x40000040};\n"
    "wgmma.mma_async.sync.aligned.m64n48k16.f32.bf16.bf16 "
    "{%0, %1, %2, %3, %4, %5, %6, %7, %8, %9, %10, %11, %12, %13, %14, %15, %16, %17, %18, %19, %20, %21, %22, %23}, "
    "{%24, %25, %26, %27}, db, p, 1, 1, 0;\n"
    "}\n"
    : "+f"(d[0]), "+f"(d[1]), "+f"(d[2]), "+f"(d[3]), "+f"(d[4]), "+f"(d[5]), "+f"(d[6]), "+f"(d[7]), "+f"(d[8]), "+f"(d[9]), "+f"(d[10]), "+f"(d[11]), "+f"(d[12]), "+f"(d[13]), "+f"(d[14]), "+f"(d[15]), "+f"(d[16]), "+f"(d[17]), "+f"(d[18]), "+f"(d[19]), "+f"(d[20]), "+f"(d[21]), "+f"(d[22]), "+f"(d[23])
    : "r"(a[0]), "r"(a[1]), "r"(a[2]), "r"(a[3]), "r"(descB), "r"(accum));
}
template <> __device__ __forceinline__ void wgmma_rs<40>(float* d, const uint32_t* a, uint32_t descB, uint32_t accum) {
  asm volatile(
    "{\n.reg .pred p;\n.reg .b64 db;\n"
    "setp.ne.b32 p, %25, 0;\n"
    "mov.b64 db, {%24, 0x40000040};\n"
    "wgmma.mma_async.sync.aligned.m64n40k16.f32.bf16.bf16 "
    "{%0, %1, %2, %3, %4, %5, %6, %7, %8, %9, %10, %11, %12, %13, %14, %15, %16, %17, %18, %19}, "
    "{%20, %21, %22, %23}, db, p, 1, 1, 0;\n"
    "}\n"
    : "+f"(d[0]), "+f"(d[1]), "+f"(d[2]), "+f"(d[3]), "+f"(d[4]), "+f"(d[5]), "+f"(d[6]), "+f"(d[7]), "+f"(d[8]), "+f"(d[9]), "+f"(d[10]), "+f"(d[11]), "+f"(d[12]), "+f"(d[13]), "+f"(d[14]), "+f"(d[15]), "+f"(d[16]), "+f"(d[17]), "+f"(d[18]), "+f"(d[19])
    : "r"(a[0]), "r"(a[1]), "r"(a[2]), "r"(a[3]), "r"(descB), "r"(accum));
}

template <int N> __device__ __forceinline__ void wgmma_ss(float* d, uint32_t descA, uint32_t descB, uint32_t accum);
template <> __device__ __forceinline__ void wgmma_ss<192>(float* d, uint32_t descA, uint32_t descB, uint32_t accum) {
  asm volatile(
    "{\n.reg .pred p;\n.reg .b64 da, db;\n"
    "setp.ne.b32 p, %98, 0;\n"
    "mov.b64 da, {%96, 0x40000040};\n"
    "mov.b64 db, {%97, 0x40000040};\n"
    "wgmma.mma_async.sync.aligned.m64n192k16.f32.bf16.bf16 "
    "{%0, %1, %2, %3, %4, %5, %6, %7, %8, %9, %10, %11, %12, %13, %14, %15, %16, %17, %18, %19, %20, %21, %22, %23, %24, %25, %26, %27, %28, %29, %30, %31, %32, %33, %34, %35, %36, %37, %38, %39, %40, %41, %42, %43, %44, %45, %46, %47, %48, %49, %50, %51, %52, %53, %54, %55, %56, %57, %58, %59, %60, %61, %62, %63, %64, %65, %66, %67, %68, %69, %70, %71, %72, %73, %74, %75, %76, %77, %78, %79, %80, %81, %82, %83, %84, %85, %86, %87, %88, %89, %90, %91, %92, %93, %94, %95}, "
    "da, db, p, 1, 1, 0, 0;\n"
    "}\n"
    : "+f"(d[0]), "+f"(d[1]), "+f"(d[2]), "+f"(d[3]), "+f"(d[4]), "+f"(d[5]), "+f"(d[6]), "+f"(d[7]), "+f"(d[8]), "+f"(d[9]), "+f"(d[10]), "+f"(d[11]), "+f"(d[12]), "+f"(d[13]), "+f"(d[14]), "+f"(d[15]), "+f"(d[16]), "+f"(d[17]), "+f"(d[18]), "+f"(d[19]), "+f"(d[20]), "+f"(d[21]), "+f"(d[22]), "+f"(d[23]), "+f"(d[24]), "+f"(d[25]), "+f"(d[26]), "+f"(d[27]), "+f"(d[28]), "+f"(d[29]), "+f"(d[30]), "+f"(d[31]), "+f"(d[32]), "+f"(d[33]), "+f"(d[34]), "+f"(d[35]), "+f"(d[36]), "+f"(d[37]), "+f"(d[38]), "+f"(d[39]), "+f"(d[40]), "+f"(d[41]), "+f"(d[42]), "+f"(d[43]), "+f"(d[44]), "+f"(d[45]), "+f"(d[46]), "+f"(d[47]), "+f"(d[48]), "+f"(d[49]), "+f"(d[50]), "+f"(d[51]), "+f"(d[52]), "+f"(d[53]), "+f"(d[54]), "+f"(d[55]), "+f"(d[56]), "+f"(d[57]), "+f"(d[58]), "+f"(d[59]), "+f"(d[60]), "+f"(d[61]), "+f"(d[62]), "+f"(d[63]), "+f"(d[64]), "+f"(d[65]), "+f"(d[66]), "+f"(d[67]), "+f"(d[68]), "+f"(d[69]), "+f"(d[70]), "+f"(d[71]), "+f"(d[72]), "+f"(d[73]), "+f"(d[74]), "+f"(d[75]), "+f"(d[76]), "+f"(d[77]), "+f"(d[78]), "+f"(d[79]), "+f"(d[80]), "+f"(d[81]), "+f"(d[82]), "+f"(d[83]), "+f"(d[84]), "+f"(d[85]), "+f"(d[86]), "+f"(d[87]), "+f"(d[88]), "+f"(d[89]), "+f"(d[90]), "+f"(d[91]), "+f"(d[92]), "+f"(d[93]), "+f"(d[94]), "+f"(d[95])
    : "r"(descA), "r"(descB), "r"(accum));
}
template <> __device__ __forceinline__ void wgmma_ss<184>(float* d, uint32_t descA, uint32_t descB, uint32_t accum) {
  asm volatile(
    "{\n.reg .pred p;\n.reg .b64 da, db;\n"
    "setp.ne.b32 p, %94, 0;\n"
    "mov.b64 da, {%92, 0x40000040};\n"
    "mov.b64 db, {%93, 0x40000040};\n"
    "wgmma.mma_async.sync.aligned.m64n184k16.f32.bf16.bf16 "
    "{%0, %1, %2, %3, %4, %5, %6, %7, %8, %9, %10, %11, %12, %13, %14, %15, %16, %17, %18, %19, %20, %21, %22, %23, %24, %25, %26, %27, %28, %29, %30, %31, %32, %33, %34, %35, %36, %37, %38, %39, %40, %41, %42, %43, %44, %45, %46, %47, %48, %49, %50, %51, %52, %53, %54, %55, %56, %57, %58, %59, %60, %61, %62, %63, %64, %65, %66, %67, %68, %69, %70, %71, %72, %73, %74, %75, %76, %77, %78, %79, %80, %81, %82, %83, %84, %85, %86, %87, %88, %89, %90, %91}, "
    "da, db, p, 1, 1, 0, 0;\n"
    "}\n"
    : "+f"(d[0]), "+f"(d[1]), "+f"(d[2]), "+f"(d[3]), "+f"(d[4]), "+f"(d[5]), "+f"(d[6]), "+f"(d[7]), "+f"(d[8]), "+f"(d[9]), "+f"(d[10]), "+f"(d[11]), "+f"(d[12]), "+f"(d[13]), "+f"(d[14]), "+f"(d[15]), "+f"(d[16]), "+f"(d[17]), "+f"(d[18]), "+f"(d[19]), "+f"(d[20]), "+f"(d[21]), "+f"(d[22]), "+f"(d[23]), "+f"(d[24]), "+f"(d[25]), "+f"(d[26]), "+f"(d[27]), "+f"(d[28]), "+f"(d[29]), "+f"(d[30]), "+f"(d[31]), "+f"(d[32]), "+f"(d[33]), "+f"(d[34]), "+f"(d[35]), "+f"(d[36]), "+f"(d[37]), "+f"(d[38]), "+f"(d[39]), "+f"(d[40]), "+f"(d[41]), "+f"(d[42]), "+f"(d[43]), "+f"(d[44]), "+f"(d[45]), "+f"(d[46]), "+f"(d[47]), "+f"(d[48]), "+f"(d[49]), "+f"(d[50]), "+f"(d[51]), "+f"(d[52]), "+f"(d[53]), "+f"(d[54]), "+f"(d[55]), "+f"(d[56]), "+f"(d[57]), "+f"(d[58]), "+f"(d[59]), "+f"(d[60]), "+f"(d[61]), "+f"(d[62]), "+f"(d[63]), "+f"(d[64]), "+f"(d[65]), "+f"(d[66]), "+f"(d[67]), "+f"(d[68]), "+f"(d[69]), "+f"(d[70]), "+f"(d[71]), "+f"(d[72]), "+f"(d[73]), "+f"(d[74]), "+f"(d[75]), "+f"(d[76]), "+f"(d[77]), "+f"(d[78]), "+f"(d[79]), "+f"(d[80]), "+f"(d[81]), "+f"(d[82]), "+f"(d[83]), "+f"(d[84]), "+f"(d[85]), "+f"(d[86]), "+f"(d[87]), "+f"(d[88]), "+f"(d[89]), "+f"(d[90]), "+f"(d[91])
    : "r"(descA), "r"(descB), "r"(accum));
}

template <int N> struct IC { static constexpr int v = N; };

__device__ __forceinline__ void stmatrix_x4_t(uint32_t addr, uint32_t r0, uint32_t r1, uint32_t r2, uint32_t r3) {
  asm volatile("stmatrix.sync.aligned.m8n8.x4.trans.shared.b16 [%0], {%1, %2, %3, %4};"
               ::"r"(addr), "r"(r0), "r"(r1), "r"(r2), "r"(r3) : "memory");
}
__device__ __forceinline__ void stmatrix_x2_t(uint32_t addr, uint32_t r0, uint32_t r1) {
  asm volatile("stmatrix.sync.aligned.m8n8.x2.trans.shared.b16 [%0], {%1, %2};" ::"r"(addr), "r"(r0), "r"(r1) : "memory");
}
__device__ __forceinline__ void ldmatrix_x4(uint32_t* r, uint32_t addr) {
  asm volatile("ldmatrix.sync.aligned.m8n8.x4.shared.b16 {%0, %1, %2, %3}, [%4];"
               : "=r"(r[0]), "=r"(r[1]), "=r"(r[2]), "=r"(r[3]) : "r"(addr) : "memory");
}
__device__ __forceinline__ uint32_t pack_bf16(float a, float b) {
  __nv_bfloat162 v = __floats2bfloat162_rn(a, b);
  return *reinterpret_cast<uint32_t*>(&v);
}
__device__ __forceinline__ uint32_t prmt(uint32_t a, uint32_t b, uint32_t s) {
  uint32_t d;
  asm("prmt.b32 %0, %1, %2, %3;" : "=r"(d) : "r"(a), "r"(b), "r"(s));
  return d;
}
__device__ __forceinline__ uint32_t lds32(uint32_t a) {
  uint32_t v;
  asm volatile("ld.shared.u32 %0, [%1];" : "=r"(v) : "r"(a) : "memory");
  return v;
}
__device__ __forceinline__ void lds64(uint32_t* v, uint32_t a) {
  asm volatile("ld.shared.v2.u32 {%0, %1}, [%2];" : "=r"(v[0]), "=r"(v[1]) : "r"(a) : "memory");
}
__device__ __forceinline__ void lds128(uint32_t* v, uint32_t a) {
  asm volatile("ld.shared.v4.u32 {%0, %1, %2, %3}, [%4];" : "=r"(v[0]), "=r"(v[1]), "=r"(v[2]), "=r"(v[3]) : "r"(a) : "memory");
}
__device__ __forceinline__ void sts128(uint32_t a, const uint32_t* v) {
  asm volatile("st.shared.v4.u32 [%0], {%1, %2, %3, %4};" ::"r"(a), "r"(v[0]), "r"(v[1]), "r"(v[2]), "r"(v[3]) : "memory");
}
__device__ __forceinline__ void wait_until(uint32_t t0, uint32_t at) {
#pragma unroll 1
  for (int r; (r = (int)(at - ((uint32_t)clock() - t0))) > 0;) __nanosleep(r >> SLS);
}
__device__ __forceinline__ uint32_t ld_acquire(const unsigned int* p) {
  uint32_t v;
  if (ACQ) asm volatile("ld.acquire.gpu.global.u32 %0, [%1];" : "=r"(v) : "l"(p) : "memory");
  else asm volatile("ld.relaxed.gpu.global.u32 %0, [%1];" : "=r"(v) : "l"(p) : "memory");
  return v;
}
__device__ __forceinline__ void wait_count(const unsigned int* f) {
#pragma unroll 1
  for (uint32_t tries = 0; ld_acquire(f) < 64u && tries < (1u << 16); tries++) __nanosleep(100);
}
__device__ __forceinline__ uint32_t ld_relaxed(const unsigned int* p) {
  uint32_t v;
  asm volatile("ld.relaxed.gpu.global.u32 %0, [%1];" : "=r"(v) : "l"(p) : "memory");
  return v;
}
template <int E>
__device__ __forceinline__ void ld_lut(uint32_t* v, const __nv_bfloat16* p) {
  asm volatile("ld.global.nc.u32 %0, [%1+%2];" : "=r"(v[E]) : "l"(p), "n"(((E & 3) * N_ + 8 * (E >> 2)) * 2));
  if constexpr (E < 7) ld_lut<E + 1>(v, p);
}
template <int E>
__device__ __forceinline__ void ld_lut16(uint32_t* v, const __nv_bfloat16* p) {
  asm volatile("ld.global.nc.u16 %0, [%1+%2];" : "=r"(v[E]) : "l"(p), "n"(E * N_ * 2));
  if constexpr (E < 15) ld_lut16<E + 1>(v, p);
}
template <int OFF>
__device__ __forceinline__ void ld_codes4_if(uint32_t* w, const int* p, uint32_t c) {
  asm volatile("{\n.reg .pred p;\nsetp.eq.u32 p, %6, 2;\n@p ld.global.nc.L1::no_allocate.v4.u32 {%0, %1, %2, %3}, [%4+%5];\n}\n"
               : "=r"(w[0]), "=r"(w[1]), "=r"(w[2]), "=r"(w[3]) : "l"(p), "n"(OFF), "r"(c));
}
template <int OFF>
__device__ __forceinline__ void ld_codes4(uint32_t* w, const int* p) {
  asm volatile("ld.global.nc.L1::no_allocate.v4.u32 {%0, %1, %2, %3}, [%4+%5];" : "=r"(w[0]), "=r"(w[1]), "=r"(w[2]), "=r"(w[3]) : "l"(p), "n"(OFF));
}
__device__ __forceinline__ void sts32(uint32_t a, uint32_t v) {
  asm volatile("st.shared.u32 [%0], %1;" ::"r"(a), "r"(v) : "memory");
}
__device__ __forceinline__ void prefetch_map(const CUtensorMap* map) {
  asm volatile("prefetch.tensormap [%0];" ::"l"((uint64_t)map) : "memory");
}
template <int OFF>
__device__ __forceinline__ void ld_words(uint32_t* w, const uint8_t* p) {
  asm volatile("ld.relaxed.gpu.global.v4.u32 {%0, %1, %2, %3}, [%4+%5];" : "=r"(w[0]), "=r"(w[1]), "=r"(w[2]), "=r"(w[3]) : "l"(p), "n"(OFF) : "memory");
}
template <int OFF>
__device__ __forceinline__ void st_words(uint8_t* p, const uint32_t* w) {
  asm volatile("st.relaxed.gpu.global.v4.u32 [%0+%5], {%1, %2, %3, %4};" ::"l"(p), "r"(w[0]), "r"(w[1]), "r"(w[2]), "r"(w[3]), "n"(OFF) : "memory");
}

#define DBG(i)

__device__ __forceinline__ uint32_t make_word(uint32_t c0, uint32_t c1, uint32_t c2, uint32_t c3, uint32_t sel, uint32_t pat) {
  const uint32_t m1 = sel == 0x4040u ? 1u : 256u, m2 = 257u - m1;
  uint32_t p01, p23, a, t1, t2;
  asm("mad.lo.u32 %0, %1, 16, %2;" : "=r"(p01) : "r"(c1), "r"(c0));
  asm("mad.lo.u32 %0, %1, 16, %2;" : "=r"(p23) : "r"(c3), "r"(c2));
  asm("mad.lo.u32 %0, %1, %2, %3;" : "=r"(a) : "r"(p23), "r"(m2), "r"(pat >> 1));
  asm("mad.lo.u32 %0, %1, %2, %3;" : "=r"(t1) : "r"(p01), "r"(m1), "r"(a));
  asm("mul.lo.u32 %0, %1, 0x800000;" : "=r"(a) : "r"(p23));
  asm("mad.lo.u32 %0, %1, 0x8000, %2;" : "=r"(t2) : "r"(p01), "r"(a));
  return (t1 | t2) & (0x44447777u | (pat >> 1));
}
struct Planes { uint32_t v[4][4]; };
__device__ __forceinline__ void lookup4(const Planes& pl, int c, uint32_t s, uint32_t& o0, uint32_t& o1, uint32_t one) {
  uint32_t s2;
  asm("{\n.reg .b16 l, h;\n.reg .b32 t;\nmov.b32 {l, h}, %1;\nmov.b32 t, {h, h};\nmul.rn.f16x2 %0, t, %2;\n}\n" : "=r"(s2) : "r"(s), "r"(one));
  const uint32_t lo = prmt(prmt(pl.v[0][2 * c], pl.v[1][2 * c], s), prmt(pl.v[2][2 * c], pl.v[3][2 * c], s), s2);
  const uint32_t hi = prmt(prmt(pl.v[0][2 * c + 1], pl.v[1][2 * c + 1], s), prmt(pl.v[2][2 * c + 1], pl.v[3][2 * c + 1], s), s2);
  o0 = prmt(lo, hi, 0x5140);
  o1 = prmt(lo, hi, 0x7362);
}
__device__ __forceinline__ void store_planes(uint32_t dst, const uint32_t* lv) {
#pragma unroll
  for (int h = 0; h < 2; h++) {
    uint32_t qp[4];
#pragma unroll
    for (int c = 0; c < 2; c++) {
      const uint32_t a = prmt(lv[4 * c], lv[4 * c + 1], h ? 0x7362 : 0x5140), b = prmt(lv[4 * c + 2], lv[4 * c + 3], h ? 0x7362 : 0x5140);
      qp[2 * c] = prmt(a, b, 0x5410);
      qp[2 * c + 1] = prmt(a, b, 0x7632);
    }
    sts128(dst + 64 * h, qp);
  }
}
__device__ __forceinline__ bool words_ok(const uint32_t* P, uint32_t tag) {
  return (P[0] & P[1] & P[2] & P[3] & P[4] & P[5] & P[6] & P[7] & tag) != 0;
}
template <int NJ>
__device__ __forceinline__ void stage_part(const float* a, uint32_t sts) {
#pragma unroll
  for (int j = 0; j < NJ; j++)
    stmatrix_x4_t(sts + 16 * j * 128, pack_bf16(a[8 * j], a[8 * j + 1]), pack_bf16(a[8 * j + 2], a[8 * j + 3]),
                  pack_bf16(a[8 * j + 4], a[8 * j + 5]), pack_bf16(a[8 * j + 6], a[8 * j + 7]));
}

template <int OFF>
__device__ __forceinline__ uint32_t lut_at(uint32_t tab, uint32_t c) {
  uint32_t v;
  asm volatile("ld.shared.u16 %0, [%1+%2];" : "=r"(v) : "r"(tab + 40 * c), "n"(OFF));
  return v;
}
template <int J>
__device__ __forceinline__ void convert_col(const uint32_t (*v)[4], uint32_t tab, uint8_t* dst) {
  uint32_t o[4];
#pragma unroll
  for (int i = 0; i < 4; i++) {
    const uint32_t a = lut_at<2 * J>(tab, v[2 * i][J]), b = lut_at<2 * J>(tab, v[2 * i + 1][J]);
    asm("mad.lo.u32 %0, %1, 65536, %2;" : "=r"(o[i]) : "r"(b), "r"(a));
  }
  st_words<2048 * J>(dst, o);
}
template <int HS>
__device__ __forceinline__ void convert_unit(uint32_t src, uint8_t* dst, uint32_t tab, int lane) {
  src += (lane & 15) * 128 + ((((lane >> 2) & 4) ^ (lane & 7)) << 4);
  dst += (lane >> 4) * 32768 + (lane & 15) * 16;
  tab += (lane >> 4) * 644;
#pragma unroll CUN
  for (int c = 0; c < 4; c++, tab += 8, dst += 8192) {
    uint32_t v[8][4];
#pragma unroll
    for (int i = 0; i < 8; i++) lds128(v[i], (src ^ (c << 4)) + (i & 3) * 2048 + (i >> 2) * HS);
    convert_col<0>(v, tab, dst);
    convert_col<1>(v, tab, dst);
    convert_col<2>(v, tab, dst);
    convert_col<3>(v, tab, dst);
  }
  __syncwarp();
}
__device__ __forceinline__ void ld_tab(uint32_t* e, const __nv_bfloat16* lut, int cg, int lane) {
  const __nv_bfloat16* s = lut + ((lane & 15) * N_ + 2048 + cg * 32 + (lane & 16));
  asm volatile("ld.global.nc.v4.u32 {%0, %1, %2, %3}, [%4];" : "=r"(e[0]), "=r"(e[1]), "=r"(e[2]), "=r"(e[3]) : "l"(s));
  asm volatile("ld.global.nc.v4.u32 {%0, %1, %2, %3}, [%4+16];" : "=r"(e[4]), "=r"(e[5]), "=r"(e[6]), "=r"(e[7]) : "l"(s));
}
__device__ __forceinline__ void st_tab(uint32_t tab, const uint32_t* e, int lane) {
#pragma unroll
  for (int i = 0; i < 8; i++) sts32(tab + (lane & 15) * 40 + (lane >> 4) * 644 + 4 * i, e[i]);
  __syncwarp();
}
__device__ __forceinline__ void tma_load_3d(uint32_t dst, const CUtensorMap* map, uint32_t bar, int c0, int c1, int c2) {
  asm volatile(
      "cp.async.bulk.tensor.3d.shared::cluster.global.mbarrier::complete_tx::bytes [%0], [%1, {%3, %4, %5}], [%2];"
      ::"r"(dst), "l"((uint64_t)map), "r"(bar), "r"(c0), "r"(c1), "r"(c2) : "memory");
}

__device__ __forceinline__ void load_first(uint32_t* cv, const int* qw, int w, int lane) {
  const int* src = qw + ((32 * w + (lane & 16) + ((lane >> 1) & 6)) * N_ + (blockIdx.x & 127) * 16 + (lane & 3) * 4);
  ld_codes4<0>(cv, src);
  ld_codes4<N_ * 4>(cv + 4, src);
  ld_codes4<N_ * 32>(cv + 8, src);
  ld_codes4<N_ * 36>(cv + 12, src);
}
__device__ __forceinline__ void pack_first(const uint32_t* cv, uint8_t* gp, uint32_t smem_base, int w, int lane) {
  uint8_t* dst = gp + (((blockIdx.x & 120) * 2 + (w >> 1)) * SLAB_BYTES + (blockIdx.x & 7) * 1024 + (w & 1) * 512 + lane * 16);
  mbar_wait(smem_base + OFF_BAR + 8 * B_EPOCH, 0);
  const uint32_t odd = lds32(smem_base + OFF_EPOCH) & 256;
  const uint32_t sel = odd ? 0x4004u : 0x4040u, pat = odd ? 0x20640000u : 0x64200000u;
  const uint32_t tb = smem_base + OFF_STG + 61440 + (w >> 1) * 1024;
  uint32_t v[4];
#pragma unroll
  for (int j = 0; j < 4; j++)
    sts32(tb + (lane & 3) * 256 + j * 64 + (lane & 12) * 4 + (w & 1) * 8 + (lane >> 4) * 4, make_word(cv[j], cv[4 + j], cv[8 + j], cv[12 + j], sel, pat));
  asm volatile("bar.sync %0, 64;" ::"r"(6 + (w >> 1)) : "memory");
  lds128(v, tb + (w & 1) * 512 + lane * 16);
  st_words<0>(dst, v);
}

__global__ void __cluster_dims__(2, 1, 1) __launch_bounds__(NTHREADS, 1)
fused_kernel(unsigned int* __restrict__ count, const __nv_bfloat16* __restrict__ lut, uint8_t* __restrict__ gp,
             const int* __restrict__ qw, const uint8_t* __restrict__ xg,
             const __grid_constant__ CUtensorMap map_q, const __grid_constant__ CUtensorMap map_xa,
             const __grid_constant__ CUtensorMap map_xb, const __grid_constant__ CUtensorMap map_o96,
             const __grid_constant__ CUtensorMap map_o32, const __grid_constant__ CUtensorMap map_q2,
             const __grid_constant__ CUtensorMap map_w) {
  extern __shared__ __align__(1024) uint8_t smem_gen[];
  const uint32_t smem_base = smem_u32(smem_gen);
  const uint32_t bar_base = smem_base + OFF_BAR;
  auto bar = [&](int i) { return bar_base + 8 * i; };

  const uint32_t t0 = clock();
  const int tid = threadIdx.x;
  uint32_t cf[16];
  {
    const int* src = qw + (((tid & 48) + ((tid >> 1) & 6)) * N_ + (blockIdx.x & 127) * 16 + (tid & 3) * 4);
    ld_codes4_if<0>(cf, src, tid >> 6);
    ld_codes4_if<N_ * 4>(cf + 4, src, tid >> 6);
    ld_codes4_if<N_ * 32>(cf + 8, src, tid >> 6);
    ld_codes4_if<N_ * 36>(cf + 12, src, tid >> 6);
  }
  const int w12 = __shfl_sync(0xffffffffu, tid >> 5, 0);
  const int wg = w12 >> 2;
  const int warp = w12 & 3;
  const int lane = tid & 31;
  const int rank = blockIdx.x & 1;
  const int cl = blockIdx.x >> 1;
  const int yi = (cl * 43) >> 8;
  const int ftb = 2 * (cl - 6 * yi) + rank;
  const bool big = cl < 48;
  const int fta = big ? ftb : 12 + (blockIdx.x & 3), toka = big ? TA * yi : min(TC * ((cl - 48) >> 1), M_ - TC);
  const int tokb = TD * yi + (TB - TD) * max(yi - 8, 0);
  const int fg = 4 * ftb;
  if (__builtin_expect(wg == 0, 1)) {
    asm volatile("setmaxnreg.dec.sync.aligned.u32 72;");
    if (warp == 0) {
      if (lane == 0) {
#pragma unroll
        for (int i = 0; i < NBARS; i++) mbar_init(bar(i), i == B_STORED || i == B_PL ? 2 : (i >> 2) == 1 || i >= B_STG ? 4 : i == B_PACKED ? NPACK : 1);
        asm volatile("fence.mbarrier_init.release.cluster;" ::: "memory");
        asm volatile("fence.proxy.async.shared::cta;" ::: "memory");
        DBG(15);
      }
      __syncwarp();
      cluster_arrive_relaxed();
      asm volatile("bar.arrive 1, 128;" ::: "memory");
      cluster_wait();
      tma_load_2d_mc_w(smem_base + rank * (TA * 64), &map_xa, bar(B_FULL), 0, toka + rank * (TA / 2), X_BYTES);
      wait_until(t0, (uint32_t)XT1);
      tma_load_2d_mc_w(smem_base + STAGE_BYTES + rank * (TA * 64), &map_xa, bar(B_FULL + 1), BK, toka + rank * (TA / 2), STAGE_BYTES);
#pragma unroll 1
      for (int n = 1; n < 2 * KBLKS - 3; n++) {
        const int stage = n & 3;
        const bool first = n < KBLKS;
        const int T = first ? TA : TB;
        const int xn = n + (n < 3);
        if (n >= 3) mbar_wait(bar(B_EMPTY + stage), ((n - 3) >> 2) & 1);
        else wait_until(t0, (uint32_t)(n == 1 ? XT2 : XT3));
        if (n != 3)
          tma_load_2d_mc_w(smem_base + (xn & 3) * STAGE_BYTES + rank * T * 64, first ? &map_xa : &map_xb, bar(B_FULL + (xn & 3)),
                           (xn & (KBLKS - 1)) * BK, (first ? toka : tokb) + rank * (T / 2), STAGE_BYTES);
        if (n <= NWG) {
          wait_until(t0, (uint32_t)(n == 1 ? WT1 : n == 2 ? WT2 : WT0 + n * WTS));
        }
        if (first) bulk_load_w(smem_base + stage * STAGE_BYTES + X_BYTES, gp + (fta * KBLKS + n) * SLAB_BYTES, SLAB_BYTES, bar(B_FULL + stage));
        else {
          tma_load_2d_w(smem_base + stage * STAGE_BYTES + TB * 128, &map_w, bar(B_FULL + stage), (n - KBLKS) * BK, ftb * BF);
          tma_load_2d_w(smem_base + stage * STAGE_BYTES + TB * 128 + 8192, &map_w, bar(B_FULL + stage), (n - KBLKS) * BK, ftb * BF + 64);
        }
        if (n == KBLKS - 1) {
          wait_count(count + 32 * (1 + ((lds32(smem_base + OFF_EPOCH) & 256) ? 48 : 0) + fg));
        }
        if (n == KBLKS + 3 || n == KBLKS + 7) mbar_wait(bar(B_RDY) + (n == KBLKS + 7 ? 8 : 0), 0);
      }
      if (lane == 0) {
        const uint32_t s1 = smem_base + STAGE_BYTES, s2 = s1 + STAGE_BYTES, s3 = s2 + STAGE_BYTES;
        mbar_wait(bar(B_EMPTY + 1), 0);
        mbar_expect_tx(bar(B_FULL + 1), STAGE_BYTES);
        tma_load_2d_mc(s1 + rank * 12288, &map_xb, bar(B_FULL + 1), (13 + rank) * BK, tokb, 3);
        tma_load_2d(s1 + 24576, &map_w, bar(B_FULL + 1), 13 * BK, ftb * BF);
        tma_load_2d(s1 + 32768, &map_w, bar(B_FULL + 1), 14 * BK, ftb * BF);
        mbar_wait(bar(B_EMPTY + 2), 0);
        mbar_expect_tx(bar(B_FULL + 2), 20480);
        if (!rank) tma_load_2d_mc(s2, &map_xb, bar(B_FULL + 2), 15 * BK, tokb, 3);
        tma_load_2d(s2 + 12288, &map_w, bar(B_FULL + 2), 15 * BK, ftb * BF);
        mbar_expect_tx(bar(B_RDY), 24576);
        tma_load_2d(s2 + 20480, &map_w, bar(B_RDY), 13 * BK, ftb * BF + 64);
        tma_load_2d(s2 + 28672, &map_w, bar(B_RDY), 14 * BK, ftb * BF + 64);
        mbar_wait(bar(B_STORED), 0);
        tma_load_2d(smem_base + OFF_STG + 24576, &map_w, bar(B_RDY), 15 * BK, ftb * BF + 64);
        mbar_wait(bar(B_EMPTY + 3), 1);
        mbar_expect_tx(bar(B_FULL + 3), 36864);
        tma_load_2d_mc(s3 + rank * 12288, &map_xb, bar(B_FULL + 3), (13 + rank) * BK, tokb + TB / 2, 3);
        if (rank) tma_load_2d_mc(s3 + 24576, &map_xb, bar(B_FULL + 3), 15 * BK, tokb + TB / 2, 3);
      }
      __syncwarp();
      mbar_wait(bar(B_PACKED), 0);
      if (lane == 0) atomicAdd(count, blockIdx.x < 2 * NUM_CTAS - 256 ? 1u : 2u);
      __syncwarp();
    } else {
      const int p = warp - 1;
      uint32_t cv[16];
      if (p == 2) {
        if (lane == 0) {
          cv[0] = ld_relaxed(count);
          prefetch_map(&map_xa); prefetch_map(&map_q);
        }
        __syncwarp();
        cluster_arrive_relaxed();
      } else {
        {
          const uint8_t* xp = xg + (((blockIdx.x & 127) * 16 + p * 8 + (lane >> 2)) * (K_ * 2) + (lane & 3) * 32);
          asm volatile("prefetch.global.L2 [%0];" ::"l"(xp));
        }
        cluster_arrive_relaxed();
        while ((uint32_t)clock() - t0 < (uint32_t)S1D) {}
        load_first(cv, qw, 2 + p, lane);
      }
      const int q = lane & 3, cq = lane >> 2;
      const uint32_t slot = smem_base + OFF_STG + p * UNIT_BYTES;
      const int g3 = blockIdx.x / 44, gi = blockIdx.x - 44 * g3;
      const int u = min(128 + 3 * gi + p + NUM_CTAS * (g3 + NPACK * (lane & 3)), 1023);
      uint32_t uo = ((((u & 63) >> 2) * KBLKS + (u >> 6)) * 4 + (u & 3)) * 2048;
      int uc0 = (u & 63) * 32, uc1 = u & ~63;
      asm volatile("" : "+r"(uo), "+r"(uc0), "+r"(uc1));
      asm volatile("bar.sync 1, 128;" ::: "memory");
      auto issue = [&](int rnd) {
        const int r = (NPACK * rnd + g3) * 44 + gi;
        const uint32_t at = D0 + min(r * (PER / 44), R1 * 44 * (PER / 44 - PER2 / 44) + r * (PER2 / 44));
        wait_until(t0, at);
        if (lane == rnd) {
          mbar_expect_tx(bar(B_SLOT + p), UNIT_BYTES);
          tma_load_2d(slot, &map_q, bar(B_SLOT + p), uc0, uc1);
        }
        __syncwarp();
      };
      const bool early = D0 + blockIdx.x * (PER / 44) < (p == 2 ? TE2 : TE);
      if (early) issue(0);
      if (p < 2) pack_first(cv, gp, smem_base, 2 + p, lane);
      else if (lane == 0) {
        asm volatile("st.shared.u32 [%0], %1;" ::"r"(smem_base + OFF_EPOCH), "r"(cv[0]) : "memory");
        mbar_arrive(bar(B_EPOCH));
        DBG(28);
      }
      __syncwarp();
      const int ne = g3 ? 2 : 3;
#pragma unroll 1
      for (int rnd = 0; rnd < ne; rnd++) {
        if (rnd > 0 || !early) issue(rnd);
        mbar_wait(bar(B_SLOT + p), rnd & 1);
        mbar_wait(bar(B_EPOCH), 0);
        const uint32_t ep = lds32(smem_base + OFF_EPOCH);
        const uint32_t ua = slot + q * 256 + ((cq ^ (2 * q)) << 4);
        const uint32_t sel = (ep & 256) ? 0x4004u : 0x4040u;
        const uint32_t pat = (ep & 256) ? 0x20640000u : 0x64200000u;
        uint32_t w[4][4];
#pragma unroll
        for (int b = 0; b < 4; b++) {
          uint32_t v[4][4];
          lds128(v[0], ua + b * 2048);
          lds128(v[1], (ua ^ 16) + b * 2048 + 128);
          lds128(v[2], ua + b * 2048 + 1024);
          lds128(v[3], (ua ^ 16) + b * 2048 + 1024 + 128);
#pragma unroll
          for (int j = 0; j < 4; j++) w[j][b] = make_word(v[0][j], v[1][j], v[2][j], v[3][j], sel, pat);
        }
        uint8_t* dst = gp + (__shfl_sync(0xffffffffu, uo, rnd) + cq * 256 + q * 16);
        st_words<0>(dst, w[0]); st_words<64>(dst, w[1]); st_words<128>(dst, w[2]); st_words<192>(dst, w[3]);
        __syncwarp();
      }
      const int l = 3 * blockIdx.x + p + (g3 ? -NUM_CTAS : 2 * NUM_CTAS);
      const int ls = (l * 1366) >> 16, cg = l - 48 * ls;
      unsigned int* cnt = count + 32 * (1 + ((lds32(smem_base + OFF_EPOCH) & 256) ? 48 : 0));
      if (l < NL) {
        uint32_t e[8];
        ld_tab(e, lut, cg, lane);
        prefetch_map(&map_q2);
        wait_until(t0, (uint32_t)(LT0 + l * LTS));
        if (lane == 0) {
          mbar_expect_tx(bar(B_SLOT + p), 2 * UNIT_BYTES);
          tma_load_3d(slot, &map_q2, bar(B_SLOT + p), 2048 + cg * 32, ls * 16, 0);
          tma_load_3d(slot + 32768, &map_q2, bar(B_SLOT + p), 2048 + cg * 32, ls * 16, 4);
        }
        const uint32_t tab = smem_base + OFF_TAB + p * 1536;
        st_tab(tab, e, lane);
        uint8_t* dst = gp + (W_OFF + cg * 65536 + ls * 256);
        mbar_wait(bar(B_SLOT + p), ne & 1);
        convert_unit<32768>(slot, dst, tab, lane);
      }
      cluster_wait();
      if (lane == 0) {
        mbar_arrive(bar(B_PACKED));
        if (l < NL) {
          asm volatile("fence.proxy.async.global;" ::: "memory");
          asm volatile("red.release.gpu.global.add.u32 [%0], %1;" ::"l"(cnt + 32 * ((cg & ~3) + min(ls >> 1, 2))), "r"(ls < 4 ? 8 : 4) : "memory");
        }
        prefetch_map(p == 0 ? &map_o96 : p == 1 ? &map_o32 : &map_xb);
        if (p == 0) prefetch_map(&map_w);
        if (p > 0) {
          mbar_wait(bar(B_STG + p - 1), 0);
          const uint32_t t1 = clock();
#pragma unroll 1
          for (int i = 0; i < TA; i += OB) {
            if (PC) wait_until(t1, max(i - FL * 32, 0) * PC / 32);
            const int r = min(i, (big ? TA : TC) - OB);
            if (!(NOST & (1 << (i / 32)))) tma_store_2d(&map_o32, smem_base + OFF_STG + (p - 1) * 32768 + r * 128, fta * BF + 64 * (p - 1), toka + r);
            bulk_commit();
          }
          bulk_wait_read<0>();
          mbar_arrive(bar(B_STORED));
#pragma unroll 1
          for (int h = 0; h < HLP; h++) {
            const int r2 = h ? (big ? TD - 96 : TB - 96) : 0;
            mbar_wait(bar(B_STG + p - 1), h ^ 1);
            tma_store_2d(&map_o96, smem_base + OFF_STG + (p - 1) * 32768 + r2 * 128, 2048 + ftb * BF + 64 * (p - 1), tokb + r2);
            bulk_commit();
          }
          if (HLP) bulk_wait_read<0>();
        } else {
          if (blockIdx.x < 48) count[32 * (50 + blockIdx.x) - (cnt - count)] = 0;
#pragma unroll 1
          for (int i = 1; i < 3; i++) {
            wait_count(cnt + 32 * (fg + i));
            mbar_arrive(bar(B_RDY - 1 + i));
          }
        }
      }
      __syncwarp();
    }
    asm volatile("exit;");
  }
  {
    const int cw = wg - 1;
    const bool leader = (tid & 127) == 0;
    if (cw == 0) {
      uint32_t cv[16];
      if (warp >= 2) {
        const __nv_bfloat16* ls = lut + (fta * BF + 4 * (lane & 3) * N_ + 64 * warp - 128 + (lane & 16) + ((lane >> 1) & 6));
        ld_lut<0>(cv, ls);
        ld_lut<0>(cv + 8, ls + 32);
      }
      cluster_arrive_relaxed();
      cluster_wait();
      if (warp >= 2) {
        const uint32_t pd = smem_base + OFF_PL + (warp & 1) * 32768 + (lane & 28) * 32 + (lane & 3) * 16;
        store_planes(pd, cv);
        store_planes(pd + 1024, cv + 8);
        __syncwarp();
        if (lane == 0) mbar_arrive(bar(B_PL));
      } else pack_first(cf, gp, smem_base, warp, lane);
    } else {
      cluster_arrive_relaxed();
    }
    asm volatile("setmaxnreg.inc.sync.aligned.u32 216;");
    uint32_t rbar = (tid & 127) < 2 ? mapa(bar(B_EMPTY), lane & 1) : 0u;
    uint32_t tg = (w12 - 4) * 1024 + lane * 16;
    uint32_t tw = smem_base + X_BYTES + tg;
    tg += (fta * KBLKS - cw) * SLAB_BYTES;
    asm volatile("" : "+r"(tw), "+r"(tg), "+r"(rbar));
    Planes pl;
    uint32_t A[16], P[8];
    float acc[TA / 2];
    const uint32_t pls = smem_base + OFF_PL + cw * 32768 + (tid & 124) * 16;
#pragma unroll
    for (int k = 0; k < 8; k++) P[k] = 0;
    sts128(tw + 3 * STAGE_BYTES, P);
    sts128(tw + 3 * STAGE_BYTES + 512, P);
#pragma unroll
    for (int k = 0; k < 8; k++) P[k] = -cw;
#pragma unroll
    for (int k = 0; k < 16; k++) pl.v[k >> 2][k & 3] = 0;
    uint32_t rel = 0, one = 0x3c003c00u, tag = 1;
    asm volatile("" : "+r"(one), "+r"(tag));
    if (cw == 1) cluster_wait();
    const uint32_t ud = __shfl_sync(0xffffffffu, make_desc(smem_base), 0);
    const uint32_t so8 = ((lane & 7) + ((lane >> 4) << 3)) * 128 + (((2 * warp + ((lane >> 3) & 1)) ^ (lane & 7)) << 4);
    {
      {
        auto tile1 = [&](auto nh) {
        uint32_t d = ud, dn, fb, par, pa;
#pragma unroll 1
        for (int n = -2 * cw; n < KBLKS; n = max(n + 1, 0)) {
          if (__builtin_expect(!words_ok(P, tag), 0)) {
            const uint8_t* p = gp + tg;
            uint32_t tries = 0;
            if (n == 0) {
              rel = rbar;
              mbar_wait(bar(B_EPOCH), 0);
              tag = (lds32(smem_base + OFF_EPOCH) & 256) ? (1u << 17) : (1u << 25);
              while ((uint32_t)clock() - t0 < (uint32_t)TP) {}
            }
#pragma unroll 1
            do {
              ld_words<0>(P, p);
              ld_words<512>(P + 4, p);
              if (n == 0) {
                mbar_wait(bar(B_PL), 0);
#pragma unroll
                for (int k = 0; k < 4; k++) lds128(pl.v[k], pls + 16 * k);
                mbar_wait(bar(B_FULL), 0);
              }
            } while (!words_ok(P, tag) && ++tries < (1u << 16));
          }
          __syncwarp();
#pragma unroll
          for (int b = 0; b < 4; b++) {
            const int m = n + 1;
            if (b == 1) {
              asm volatile("mad.lo.u32 %0, %1, %3, %2;" : "=r"(dn) : "r"(m & 3), "r"(ud), "n"(STAGE_BYTES / 16));
              asm volatile("mad.lo.u32 %0, %1, 8, %2;" : "=r"(fb) : "r"(m & 3), "r"(bar(B_FULL)));
              asm volatile("bfe.u32 %0, %1, 2, 1;" : "=r"(par) : "r"(m));
              asm volatile("mad.lo.u32 %0, %1, %3, %2;" : "=r"(pa) : "r"(m & 3), "r"(tw), "n"(STAGE_BYTES));
            }
            if (b == WB && (!SKW || n != KBLKS - 1)) mbar_wait(fb, par);
            if (NOLK & (1 << b)) {
              A[4 * b] = P[b] * tag; A[4 * b + 2] = P[b] * tg; A[4 * b + 1] = P[4 + b] * tag; A[4 * b + 3] = P[4 + b] * tg;
            } else {
              lookup4(pl, 0, P[b], A[4 * b], A[4 * b + 2], one);
              lookup4(pl, 1, P[4 + b], A[4 * b + 1], A[4 * b + 3], one);
            }
            if (b == 3) {
              lds128(P, pa);
              lds128(P + 4, pa + 512);
              tg += SLAB_BYTES;
            }
            if (WAITS & (1 << ((b + 3) & 3))) wgmma_wait<1>();
            if (b == 1) mbar_arrive_remote_if(rel + 8 * ((n - 1) & 3), rel);
            if (S1 && b == S1B && n == KBLKS - S1 && cw == S1W) asm volatile("bar.sync 9, 256;" ::: "memory");
            wgmma_fence();
            wgmma_rs<decltype(nh)::v>(acc + TB / 2, A + 4 * b, d + 2 * b + TB * 8, b > 0 || n != 0);
            if (SPC) { wgmma_commit(); wgmma_fence(); }
            wgmma_rs<TB>(acc, A + 4 * b, d + 2 * b, b > 0 || n != 0);
            wgmma_commit();
          }
          d = n < 0 ? ud : dn;
        }
        };
        if (big) tile1(IC<TA - TB>()); else tile1(IC<TC - TB>());
        if (S1 && cw != S1W) asm volatile("bar.arrive 9, 256;" ::: "memory");
      }
      mbar_wait(bar(B_PACKED), 0);
      wgmma_wait<0>();
      mbar_arrive_remote_if(rel + 24, rel);
      fence_regs(acc);
      stage_part<16>(acc, smem_base + OFF_STG + cw * 32768 + so8);
      asm volatile("fence.proxy.async.shared::cta;" ::: "memory");
      __syncwarp();
      if (lane == 0) mbar_arrive(bar(B_STG + cw));
      {
        const uint32_t ua = ud + (TB * 8 + cw * 512);
        constexpr int ns = KBLKS - 3;
        auto tile2 = [&](auto nt) {
#pragma unroll 1
        for (int n = 0; n < ns; n++) {
          const uint32_t so = (n & 3) * (STAGE_BYTES / 16);
          mbar_wait(bar(B_FULL) + 8 * (n & 3), (n >> 2) & 1);
          wgmma_fence();
          wgmma_ss<decltype(nt)::v>(acc, ua + so, ud + so, n != 0);
          wgmma_commit();
          wgmma_wait<1>();
          mbar_arrive_remote_if(rel + 8 * ((n - 1) & 3), n ? rel : 0u);
#pragma unroll
          for (int b = 1; b < 4; b++) wgmma_ss<decltype(nt)::v>(acc, ua + so + 2 * b, ud + so + 2 * b, 1);
          wgmma_commit();
        }
        };
        if (big) tile2(IC<TD>()); else tile2(IC<TB>());
        uint32_t W[48];
        float c2[TB / 2];
        const uint32_t wa = smem_base + (warp * 16 + (lane & 15)) * 128 + (((lane >> 4) ^ (lane & 7)) << 4);
        const uint32_t w0 = wa + (cw ? 2 * STAGE_BYTES + 20480 : STAGE_BYTES + 24576), w2 = wa + (cw ? OFF_STG + 24576 : 2 * STAGE_BYTES + 12288);
        mbar_wait(bar(B_FULL + 1), 1);
        if (cw) mbar_wait(bar(B_RDY), 1);
#pragma unroll
        for (int b = 0; b < 8; b++) ldmatrix_x4(W + 4 * b, (w0 ^ ((b & 3) << 5)) + (b >> 2) * 8192);
        wgmma_wait<0>();
#pragma unroll
        for (int k = 0; k < TB / 2; k++) asm volatile("mov.b32 %0, %1;" : "=f"(c2[k]) : "f"(acc[k]) : "memory");
        const uint32_t stg = smem_base + OFF_STG + cw * 32768;
#pragma unroll
        for (int h = 0; h < 2; h++) {
          if (h) mbar_wait(bar(B_FULL + 3), 1);
          if (h || cw) asm volatile("bar.sync %0, 256;" ::"r"(9 + 2 * h + cw) : "memory");
          auto half = [&](auto nn) {
          wgmma_fence();
#pragma unroll
          for (int i = 0; i < 12; i++) {
            if (h == 0 && i == 8) {
              mbar_wait(bar(B_FULL + 2), 1);
#pragma unroll
              for (int b = 0; b < 4; b++) ldmatrix_x4(W + 32 + 4 * b, w2 ^ (b << 5));
              wgmma_fence();
            }
            wgmma_rs<decltype(nn)::v>(c2 + 48 * h, W + 4 * i, ud + (h ? 3 * STAGE_BYTES + (i >> 2) * 12288 : i < 8 ? STAGE_BYTES + (i >> 2) * 12288 : 2 * STAGE_BYTES) / 16 + 2 * (i & 3), 1);
            if (i == NSI - 1) wgmma_commit();
          }
          wgmma_commit();
          };
          if (N88 && h && big) half(IC<TD - TB / 2>()); else half(IC<TB / 2>());
          wgmma_wait<1>();
          if (!h || !cw) asm volatile("bar.arrive %0, 256;" ::"r"(10 + 2 * h + cw) : "memory");
          if (!h) mbar_wait(bar(B_STORED), 0);
          wgmma_wait<0>();
#pragma unroll
          for (int k = 0; k < 48; k++) asm volatile("" : "+f"(c2[48 * h + k]) :: "memory");
          stage_part<6>(c2 + 48 * h, stg + so8 + 96 * 128 * h);
          asm volatile("fence.proxy.async.shared::cta;" ::: "memory");
          if (h < HLP) {
            __syncwarp();
            if (lane == 0) mbar_arrive(bar(B_STG + cw));
          } else {
            asm volatile("bar.sync %0, 128;" ::"r"(2 + cw) : "memory");
            if (leader) {
              const int r2 = h ? (big ? TD - 96 : TB - 96) : 0;
              tma_store_2d(&map_o96, stg + r2 * 128, 2048 + ftb * BF + 64 * cw, tokb + r2);
              bulk_commit();
            }
          }
          __syncwarp();
        }
      }
    }
    if (leader && HLP < 2) {
      bulk_wait_read<0>();
    }
  }
}

typedef CUresult (*EncodeFn)(CUtensorMap*, CUtensorMapDataType, cuuint32_t, void*, const cuuint64_t*, const cuuint64_t*,
                             const cuuint32_t*, const cuuint32_t*, CUtensorMapInterleave, CUtensorMapSwizzle,
                             CUtensorMapL2promotion, CUtensorMapFloatOOBfill);

}

extern "C" void kernel_launch(void* const* d_in, const int* in_sizes, int n_in, void* d_out, int out_size) {
  const __nv_bfloat16* x = (const __nv_bfloat16*)d_in[0];
  const int* qw = (const int*)d_in[1];
  const __nv_bfloat16* lut = (const __nv_bfloat16*)d_in[2];

  static EncodeFn enc = nullptr;
  static unsigned int* count = nullptr;
  static uint8_t* gp = nullptr;
  if (!enc) {
    cudaDriverEntryPointQueryResult q;
    void* fn = nullptr;
    cudaGetDriverEntryPoint("cuTensorMapEncodeTiled", &fn, cudaEnableDefault, &q);
    enc = (EncodeFn)fn;
    cudaGetSymbolAddress((void**)&count, g_count);
    cudaGetSymbolAddress((void**)&gp, g_p);
    cudaFuncSetAttribute(fused_kernel, cudaFuncAttributeMaxDynamicSharedMemorySize, SMEM_BYTES);
  }
  CUtensorMap map_xa, map_xb, map_o96, map_o32, map_q, map_q2, map_w;
  for (int i = 0; i < 2; i++) {
    cuuint64_t dims[2] = {(cuuint64_t)K_, (cuuint64_t)M_};
    cuuint64_t strides[1] = {(cuuint64_t)K_ * 2};
    cuuint32_t box[2] = {BK, (cuuint32_t)(i ? TB / 2 : TA / 2)};
    cuuint32_t es[2] = {1, 1};
    enc(i ? &map_xb : &map_xa, CU_TENSOR_MAP_DATA_TYPE_BFLOAT16, 2, (void*)x, dims, strides, box, es, CU_TENSOR_MAP_INTERLEAVE_NONE,
        CU_TENSOR_MAP_SWIZZLE_128B, XPROM, CU_TENSOR_MAP_FLOAT_OOB_FILL_NONE);
  }
  for (int i = 0; i < 2; i++) {
    cuuint64_t dims[2] = {(cuuint64_t)N_, (cuuint64_t)M_};
    cuuint64_t strides[1] = {(cuuint64_t)N_ * 2};
    cuuint32_t box[2] = {64, (cuuint32_t)(i ? OB : 96)};
    cuuint32_t es[2] = {1, 1};
    enc(i ? &map_o32 : &map_o96, CU_TENSOR_MAP_DATA_TYPE_BFLOAT16, 2, d_out, dims, strides, box, es, CU_TENSOR_MAP_INTERLEAVE_NONE,
        CU_TENSOR_MAP_SWIZZLE_128B, CU_TENSOR_MAP_L2_PROMOTION_NONE, CU_TENSOR_MAP_FLOAT_OOB_FILL_NONE);
  }
  {
    cuuint64_t dims[2] = {(cuuint64_t)N_, (cuuint64_t)K_};
    cuuint64_t strides[1] = {(cuuint64_t)N_ * 4};
    cuuint32_t box[2] = {32u, BK};
    cuuint32_t es[2] = {1, 1};
    enc(&map_q, CU_TENSOR_MAP_DATA_TYPE_INT32, 2, (void*)qw, dims, strides, box, es, CU_TENSOR_MAP_INTERLEAVE_NONE,
        CU_TENSOR_MAP_SWIZZLE_128B, QPROM, CU_TENSOR_MAP_FLOAT_OOB_FILL_NONE);
  }
  {
    cuuint64_t dims[3] = {(cuuint64_t)N_, (cuuint64_t)K_ / 8, 8};
    cuuint64_t strides[2] = {(cuuint64_t)N_ * 32, (cuuint64_t)N_ * 4};
    cuuint32_t box[3] = {32, 16, 4};
    cuuint32_t es[3] = {1, 1, 1};
    enc(&map_q2, CU_TENSOR_MAP_DATA_TYPE_INT32, 3, (void*)qw, dims, strides, box, es, CU_TENSOR_MAP_INTERLEAVE_NONE,
        CU_TENSOR_MAP_SWIZZLE_128B, QPROM, CU_TENSOR_MAP_FLOAT_OOB_FILL_NONE);
  }
  {
    cuuint64_t dims[2] = {(cuuint64_t)K_, (cuuint64_t)(N_ - 2048)};
    cuuint64_t strides[1] = {(cuuint64_t)K_ * 2};
    cuuint32_t box[2] = {BK, 64};
    cuuint32_t es[2] = {1, 1};
    enc(&map_w, CU_TENSOR_MAP_DATA_TYPE_BFLOAT16, 2, (void*)(gp + W_OFF), dims, strides, box, es, CU_TENSOR_MAP_INTERLEAVE_NONE,
        CU_TENSOR_MAP_SWIZZLE_128B, XPROM, CU_TENSOR_MAP_FLOAT_OOB_FILL_NONE);
  }
  fused_kernel<<<NUM_CTAS, NTHREADS, SMEM_BYTES, cudaStreamPerThread>>>(count, lut, gp, qw, (const uint8_t*)x, map_q, map_xa, map_xb, map_o96, map_o32, map_q2, map_w);
}
```

```cpp
#include <cuda_runtime.h>
#include <cuda_bf16.h>
#include <cuda.h>
#include <stdint.h>
#include <cstdio>
#include <algorithm>

namespace {

constexpr int M_ = 2048, K_ = 1024, N_ = 3584;
constexpr int BF = 128, BK = 64;
constexpr int TA = 256, TB = 192;
#define TCC 232
constexpr int TC = TCC, TD = 184;
constexpr int STAGES = 4;
constexpr int KBLKS = K_ / BK;
constexpr int X_BYTES = TA * BK * 2;
constexpr int UNIT_BYTES = BK * 32 * 4;
constexpr int SLAB_BYTES = BF * BK;
constexpr int STAGE_BYTES = X_BYTES + SLAB_BYTES;
constexpr int OFF_STG = STAGES * STAGE_BYTES;
constexpr int OFF_PL = OFF_STG + 3 * UNIT_BYTES;
constexpr int OFF_TAB = OFF_PL + 2048;
constexpr int OFF_BAR = OFF_STG + 65536;
constexpr int W_OFF = 16 * KBLKS * SLAB_BYTES;
constexpr int SMEM_BYTES = OFF_BAR + 512;
constexpr int NUM_CTAS = 132;
constexpr int NTHREADS = 384;
constexpr int NPACK = 3;
#define XT0 1400
#define WT0 2350
#define WTS 1000
#define NWG 5
#define S1D 400
#define PC 900
#define OB 32
#define WAITS 7
#define D0 600
#define PER 27
#define PER2 20
#define R1 308
#define WB 1
#define LT0 7000
#define LTS 18
#define XPROM CU_TENSOR_MAP_L2_PROMOTION_L2_128B
#define QPROM CU_TENSOR_MAP_L2_PROMOTION_L2_128B
#define S1B 1
#define S1N 15
#define NP 2
#define PN 16
#define MI 6
#define EP1 1
#define EP2 4
#define UPF 0
#define W17 1
#define SB0 0
#define NSB 8
#define FEN 1
#define NSI 10
#define N88 1
#define GMAP 1
#define CK2 0
#define SAL 0
#define O24 1
#define NSH 2
static_assert(SMEM_BYTES <= 232448, "smem");
static_assert(TB * 128 + 2 * SLAB_BYTES == STAGE_BYTES, "stage");
constexpr int B_FULL = 0, B_EMPTY = 4, B_DIR = 8, B_SLOT = 9, NBARS = 12, B_LAST = 16, B_RDY = B_DIR;
constexpr int OFF_EPOCH = OFF_BAR + 8 * NBARS;
constexpr uint32_t SB = 1024;
constexpr uint32_t UD = (SB >> 4) | (1u << 16);
enum { M_Q, M_XA, M_D, M_XB, M_O96, M_O32, M_W, M_Q2, NMAPS };

__device__ __align__(1024) uint8_t g_p[W_OFF + 12 * KBLKS * 2 * SLAB_BYTES];
__device__ __align__(128) unsigned int g_count[32 * 97];

__device__ __forceinline__ uint32_t smem_u32(const void* p) { return (uint32_t)__cvta_generic_to_shared(p); }
__device__ __forceinline__ void mbar_init(uint32_t bar, uint32_t cnt) {
  asm volatile("mbarrier.init.shared::cta.b64 [%0], %1;" ::"r"(bar), "r"(cnt) : "memory");
}
__device__ __forceinline__ void mbar_wait(uint32_t bar, uint32_t parity, uint32_t& c) {
  asm volatile(
      "{\n.reg .pred p;\n"
      "SPIN:\n"
      "mbarrier.try_wait.parity.shared::cta.b64 p, [%1], %2;\n"
      "add.u32 %0, %0, 1;\n"
      "setp.ge.or.u32 p, %0, 0x100000, p;\n"
      "@!p bra.uni SPIN;\n}\n"
      : "+r"(c) : "r"(bar), "r"(parity) : "memory");
}
__device__ __forceinline__ void mbar_wait_fast(uint32_t bar, uint32_t parity, uint32_t& c) {
  asm volatile(
      "{\n.reg .pred p;\n"
      "SPIN:\n"
      "mbarrier.try_wait.parity.shared::cta.b64 p, [%1], %2;\n"
      "@p bra.uni DONE;\n"
      "add.u32 %0, %0, 1;\n"
      "setp.lt.u32 p, %0, 0x100000;\n"
      "@p bra.uni SPIN;\n"
      "DONE:\n}\n"
      : "+r"(c) : "r"(bar), "r"(parity) : "memory");
}
__device__ __forceinline__ bool mbar_test(uint32_t bar, uint32_t parity) {
  uint32_t ok;
  asm volatile("{\n.reg .pred p;\nmbarrier.try_wait.parity.shared::cta.b64 p, [%1], %2;\nselp.u32 %0, 1, 0, p;\n}\n" : "=r"(ok) : "r"(bar), "r"(parity) : "memory");
  return ok != 0;
}
__device__ __forceinline__ void mbar_arrive(uint32_t bar) {
  asm volatile("mbarrier.arrive.shared::cta.b64 _, [%0];" ::"r"(bar) : "memory");
}
__device__ __forceinline__ uint32_t mapa(uint32_t a, uint32_t cta) {
  uint32_t r;
  asm("mapa.shared::cluster.u32 %0, %1, %2;" : "=r"(r) : "r"(a), "r"(cta));
  return r;
}
__device__ __forceinline__ void mbar_arrive_remote_if(uint32_t ra, uint32_t cond) {
  asm volatile("{\n.reg .pred p;\nsetp.ne.u32 p, %1, 0;\n@p mbarrier.arrive.shared::cluster.b64 _, [%0];\n}\n" ::"r"(ra), "r"(cond) : "memory");
}
#define ELECT "{\n.reg .pred p;\nelect.sync _|p, 0xffffffff;\n"
__device__ __forceinline__ void expect_w(uint32_t bar, uint32_t bytes) {
  asm volatile(ELECT "@p mbarrier.arrive.expect_tx.shared::cta.b64 _, [%0], %1;\n}\n" ::"r"(bar), "r"(bytes) : "memory");
}
__device__ __forceinline__ void arrive_w(uint32_t bar) {
  asm volatile(ELECT "@p mbarrier.arrive.shared::cta.b64 _, [%0];\n}\n" ::"r"(bar) : "memory");
}
__device__ __forceinline__ void tma_mc_w(uint32_t dst, const CUtensorMap* map, uint32_t bar, int c0, int c1) {
  asm volatile(
      ELECT "@p cp.async.bulk.tensor.2d.shared::cluster.global.mbarrier::complete_tx::bytes.multicast::cluster [%0], [%1, {%3, %4}], [%2], %5;\n}\n"
      ::"r"(dst), "l"((uint64_t)map), "r"(bar), "r"(c0), "r"(c1), "h"((uint16_t)3) : "memory");
}
__device__ __forceinline__ void bulk_w(uint32_t dst, const void* src, uint32_t bytes, uint32_t bar) {
  asm volatile(ELECT "@p cp.async.bulk.shared::cluster.global.mbarrier::complete_tx::bytes [%0], [%1], %2, [%3];\n}\n"
               ::"r"(dst), "l"(src), "r"(bytes), "r"(bar) : "memory");
}
__device__ __forceinline__ void tma_w(uint32_t dst, const CUtensorMap* map, uint32_t bar, int c0, int c1) {
  asm volatile(
      ELECT "@p cp.async.bulk.tensor.2d.shared::cluster.global.mbarrier::complete_tx::bytes [%0], [%1, {%3, %4}], [%2];\n}\n"
      ::"r"(dst), "l"((uint64_t)map), "r"(bar), "r"(c0), "r"(c1) : "memory");
}
__device__ __forceinline__ void tma3_w(uint32_t dst, const CUtensorMap* map, uint32_t bar, int c0, int c1, int c2) {
  asm volatile(
      ELECT "@p cp.async.bulk.tensor.3d.shared::cluster.global.mbarrier::complete_tx::bytes [%0], [%1, {%3, %4, %5}], [%2];\n}\n"
      ::"r"(dst), "l"((uint64_t)map), "r"(bar), "r"(c0), "r"(c1), "r"(c2) : "memory");
}
__device__ __forceinline__ void store_w(const CUtensorMap* map, uint32_t src, int c0, int c1) {
  asm volatile(ELECT "@p cp.async.bulk.tensor.2d.global.shared::cta.bulk_group [%0, {%2, %3}], [%1];\n}\n"
               "cp.async.bulk.commit_group;"
               ::"l"((uint64_t)map), "r"(src), "r"(c0), "r"(c1) : "memory");
}
__device__ __forceinline__ void bulk_wait_read() { asm volatile("cp.async.bulk.wait_group.read 0;" ::: "memory"); }
__device__ __forceinline__ void cluster_arrive_relaxed() { asm volatile("barrier.cluster.arrive.relaxed.aligned;" ::: "memory"); }
__device__ __forceinline__ void cluster_wait() { asm volatile("barrier.cluster.wait.acquire.aligned;" ::: "memory"); }
__device__ __forceinline__ void wgmma_fence() { asm volatile("wgmma.fence.sync.aligned;" ::: "memory"); }
__device__ __forceinline__ void wgmma_commit() { asm volatile("wgmma.commit_group.sync.aligned;" ::: "memory"); }
template <int N> __device__ __forceinline__ void wgmma_wait() { asm volatile("wgmma.wait_group.sync.aligned %0;" ::"n"(N) : "memory"); }
template <int N> __device__ __forceinline__ void fence_regs(float (&p)[N]) {
#pragma unroll
  for (int i = 0; i < N; i++) asm volatile("" : "+f"(p[i]) :: "memory");
}

template <int N> __device__ __forceinline__ void wgmma_rs(float* d, const uint32_t* a, uint32_t descB, uint32_t accum);
template <> __device__ __forceinline__ void wgmma_rs<192>(float* d, const uint32_t* a, uint32_t descB, uint32_t accum) {
  asm volatile(
    "{\n.reg .pred p;\n.reg .b64 db;\n"
    "setp.ne.b32 p, %101, 0;\n"
    "mov.b64 db, {%100, 0x40000040};\n"
    "wgmma.mma_async.sync.aligned.m64n192k16.f32.bf16.bf16 "
    "{%0, %1, %2, %3, %4, %5, %6, %7, %8, %9, %10, %11, %12, %13, %14, %15, %16, %17, %18, %19, %20, %21, %22, %23, %24, %25, %26, %27, %28, %29, %30, %31, %32, %33, %34, %35, %36, %37, %38, %39, %40, %41, %42, %43, %44, %45, %46, %47, %48, %49, %50, %51, %52, %53, %54, %55, %56, %57, %58, %59, %60, %61, %62, %63, %64, %65, %66, %67, %68, %69, %70, %71, %72, %73, %74, %75, %76, %77, %78, %79, %80, %81, %82, %83, %84, %85, %86, %87, %88, %89, %90, %91, %92, %93, %94, %95}, "
    "{%96, %97, %98, %99}, db, p, 1, 1, 0;\n"
    "}\n"
    : "+f"(d[0]), "+f"(d[1]), "+f"(d[2]), "+f"(d[3]), "+f"(d[4]), "+f"(d[5]), "+f"(d[6]), "+f"(d[7]), "+f"(d[8]), "+f"(d[9]), "+f"(d[10]), "+f"(d[11]), "+f"(d[12]), "+f"(d[13]), "+f"(d[14]), "+f"(d[15]), "+f"(d[16]), "+f"(d[17]), "+f"(d[18]), "+f"(d[19]), "+f"(d[20]), "+f"(d[21]), "+f"(d[22]), "+f"(d[23]), "+f"(d[24]), "+f"(d[25]), "+f"(d[26]), "+f"(d[27]), "+f"(d[28]), "+f"(d[29]), "+f"(d[30]), "+f"(d[31]), "+f"(d[32]), "+f"(d[33]), "+f"(d[34]), "+f"(d[35]), "+f"(d[36]), "+f"(d[37]), "+f"(d[38]), "+f"(d[39]), "+f"(d[40]), "+f"(d[41]), "+f"(d[42]), "+f"(d[43]), "+f"(d[44]), "+f"(d[45]), "+f"(d[46]), "+f"(d[47]), "+f"(d[48]), "+f"(d[49]), "+f"(d[50]), "+f"(d[51]), "+f"(d[52]), "+f"(d[53]), "+f"(d[54]), "+f"(d[55]), "+f"(d[56]), "+f"(d[57]), "+f"(d[58]), "+f"(d[59]), "+f"(d[60]), "+f"(d[61]), "+f"(d[62]), "+f"(d[63]), "+f"(d[64]), "+f"(d[65]), "+f"(d[66]), "+f"(d[67]), "+f"(d[68]), "+f"(d[69]), "+f"(d[70]), "+f"(d[71]), "+f"(d[72]), "+f"(d[73]), "+f"(d[74]), "+f"(d[75]), "+f"(d[76]), "+f"(d[77]), "+f"(d[78]), "+f"(d[79]), "+f"(d[80]), "+f"(d[81]), "+f"(d[82]), "+f"(d[83]), "+f"(d[84]), "+f"(d[85]), "+f"(d[86]), "+f"(d[87]), "+f"(d[88]), "+f"(d[89]), "+f"(d[90]), "+f"(d[91]), "+f"(d[92]), "+f"(d[93]), "+f"(d[94]), "+f"(d[95])
    : "r"(a[0]), "r"(a[1]), "r"(a[2]), "r"(a[3]), "r"(descB), "r"(accum));
}
template <> __device__ __forceinline__ void wgmma_rs<88>(float* d, const uint32_t* a, uint32_t descB, uint32_t accum) {
  asm volatile(
    "{\n.reg .pred p;\n.reg .b64 db;\n"
    "setp.ne.b32 p, %49, 0;\n"
    "mov.b64 db, {%48, 0x40000040};\n"
    "wgmma.mma_async.sync.aligned.m64n88k16.f32.bf16.bf16 "
    "{%0, %1, %2, %3, %4, %5, %6, %7, %8, %9, %10, %11, %12, %13, %14, %15, %16, %17, %18, %19, %20, %21, %22, %23, %24, %25, %26, %27, %28, %29, %30, %31, %32, %33, %34, %35, %36, %37, %38, %39, %40, %41, %42, %43}, "
    "{%44, %45, %46, %47}, db, p, 1, 1, 0;\n"
    "}\n"
    : "+f"(d[0]), "+f"(d[1]), "+f"(d[2]), "+f"(d[3]), "+f"(d[4]), "+f"(d[5]), "+f"(d[6]), "+f"(d[7]), "+f"(d[8]), "+f"(d[9]), "+f"(d[10]), "+f"(d[11]), "+f"(d[12]), "+f"(d[13]), "+f"(d[14]), "+f"(d[15]), "+f"(d[16]), "+f"(d[17]), "+f"(d[18]), "+f"(d[19]), "+f"(d[20]), "+f"(d[21]), "+f"(d[22]), "+f"(d[23]), "+f"(d[24]), "+f"(d[25]), "+f"(d[26]), "+f"(d[27]), "+f"(d[28]), "+f"(d[29]), "+f"(d[30]), "+f"(d[31]), "+f"(d[32]), "+f"(d[33]), "+f"(d[34]), "+f"(d[35]), "+f"(d[36]), "+f"(d[37]), "+f"(d[38]), "+f"(d[39]), "+f"(d[40]), "+f"(d[41]), "+f"(d[42]), "+f"(d[43])
    : "r"(a[0]), "r"(a[1]), "r"(a[2]), "r"(a[3]), "r"(descB), "r"(accum));
}
template <> __device__ __forceinline__ void wgmma_rs<64>(float* d, const uint32_t* a, uint32_t descB, uint32_t accum) {
  asm volatile(
    "{\n.reg .pred p;\n.reg .b64 db;\n"
    "setp.ne.b32 p, %37, 0;\n"
    "mov.b64 db, {%36, 0x40000040};\n"
    "wgmma.mma_async.sync.aligned.m64n64k16.f32.bf16.bf16 "
    "{%0, %1, %2, %3, %4, %5, %6, %7, %8, %9, %10, %11, %12, %13, %14, %15, %16, %17, %18, %19, %20, %21, %22, %23, %24, %25, %26, %27, %28, %29, %30, %31}, "
    "{%32, %33, %34, %35}, db, p, 1, 1, 0;\n"
    "}\n"
    : "+f"(d[0]), "+f"(d[1]), "+f"(d[2]), "+f"(d[3]), "+f"(d[4]), "+f"(d[5]), "+f"(d[6]), "+f"(d[7]), "+f"(d[8]), "+f"(d[9]), "+f"(d[10]), "+f"(d[11]), "+f"(d[12]), "+f"(d[13]), "+f"(d[14]), "+f"(d[15]), "+f"(d[16]), "+f"(d[17]), "+f"(d[18]), "+f"(d[19]), "+f"(d[20]), "+f"(d[21]), "+f"(d[22]), "+f"(d[23]), "+f"(d[24]), "+f"(d[25]), "+f"(d[26]), "+f"(d[27]), "+f"(d[28]), "+f"(d[29]), "+f"(d[30]), "+f"(d[31])
    : "r"(a[0]), "r"(a[1]), "r"(a[2]), "r"(a[3]), "r"(descB), "r"(accum));
}
template <> __device__ __forceinline__ void wgmma_rs<40>(float* d, const uint32_t* a, uint32_t descB, uint32_t accum) {
  asm volatile(
    "{\n.reg .pred p;\n.reg .b64 db;\n"
    "setp.ne.b32 p, %25, 0;\n"
    "mov.b64 db, {%24, 0x40000040};\n"
    "wgmma.mma_async.sync.aligned.m64n40k16.f32.bf16.bf16 "
    "{%0, %1, %2, %3, %4, %5, %6, %7, %8, %9, %10, %11, %12, %13, %14, %15, %16, %17, %18, %19}, "
    "{%20, %21, %22, %23}, db, p, 1, 1, 0;\n"
    "}\n"
    : "+f"(d[0]), "+f"(d[1]), "+f"(d[2]), "+f"(d[3]), "+f"(d[4]), "+f"(d[5]), "+f"(d[6]), "+f"(d[7]), "+f"(d[8]), "+f"(d[9]), "+f"(d[10]), "+f"(d[11]), "+f"(d[12]), "+f"(d[13]), "+f"(d[14]), "+f"(d[15]), "+f"(d[16]), "+f"(d[17]), "+f"(d[18]), "+f"(d[19])
    : "r"(a[0]), "r"(a[1]), "r"(a[2]), "r"(a[3]), "r"(descB), "r"(accum));
}

template <int N> __device__ __forceinline__ void wgmma_rl(float* d, const uint32_t* a, uint64_t descB);
template <> __device__ __forceinline__ void wgmma_rl<96>(float* d, const uint32_t* a, uint64_t descB) {
  asm volatile(
    "wgmma.mma_async.sync.aligned.m64n96k16.f32.bf16.bf16 "
    "{%0, %1, %2, %3, %4, %5, %6, %7, %8, %9, %10, %11, %12, %13, %14, %15, %16, %17, %18, %19, %20, %21, %22, %23, %24, %25, %26, %27, %28, %29, %30, %31, %32, %33, %34, %35, %36, %37, %38, %39, %40, %41, %42, %43, %44, %45, %46, %47}, "
    "{%48, %49, %50, %51}, %52, 1, 1, 1, 0;\n"
    : "+f"(d[0]), "+f"(d[1]), "+f"(d[2]), "+f"(d[3]), "+f"(d[4]), "+f"(d[5]), "+f"(d[6]), "+f"(d[7]), "+f"(d[8]), "+f"(d[9]), "+f"(d[10]), "+f"(d[11]), "+f"(d[12]), "+f"(d[13]), "+f"(d[14]), "+f"(d[15]), "+f"(d[16]), "+f"(d[17]), "+f"(d[18]), "+f"(d[19]), "+f"(d[20]), "+f"(d[21]), "+f"(d[22]), "+f"(d[23]), "+f"(d[24]), "+f"(d[25]), "+f"(d[26]), "+f"(d[27]), "+f"(d[28]), "+f"(d[29]), "+f"(d[30]), "+f"(d[31]), "+f"(d[32]), "+f"(d[33]), "+f"(d[34]), "+f"(d[35]), "+f"(d[36]), "+f"(d[37]), "+f"(d[38]), "+f"(d[39]), "+f"(d[40]), "+f"(d[41]), "+f"(d[42]), "+f"(d[43]), "+f"(d[44]), "+f"(d[45]), "+f"(d[46]), "+f"(d[47])
    : "r"(a[0]), "r"(a[1]), "r"(a[2]), "r"(a[3]), "l"(descB));
}

template <int N> __device__ __forceinline__ void wgmma_ss(float* d, uint64_t descA, uint64_t descB, uint32_t accum);
template <> __device__ __forceinline__ void wgmma_ss<192>(float* d, uint64_t descA, uint64_t descB, uint32_t accum) {
  asm volatile(
    "{\n.reg .pred p;\n"
    "setp.ne.b32 p, %98, 0;\n"
    "wgmma.mma_async.sync.aligned.m64n192k16.f32.bf16.bf16 "
    "{%0, %1, %2, %3, %4, %5, %6, %7, %8, %9, %10, %11, %12, %13, %14, %15, %16, %17, %18, %19, %20, %21, %22, %23, %24, %25, %26, %27, %28, %29, %30, %31, %32, %33, %34, %35, %36, %37, %38, %39, %40, %41, %42, %43, %44, %45, %46, %47, %48, %49, %50, %51, %52, %53, %54, %55, %56, %57, %58, %59, %60, %61, %62, %63, %64, %65, %66, %67, %68, %69, %70, %71, %72, %73, %74, %75, %76, %77, %78, %79, %80, %81, %82, %83, %84, %85, %86, %87, %88, %89, %90, %91, %92, %93, %94, %95}, "
    "%96, %97, p, 1, 1, 0, 0;\n"
    "}\n"
    : "+f"(d[0]), "+f"(d[1]), "+f"(d[2]), "+f"(d[3]), "+f"(d[4]), "+f"(d[5]), "+f"(d[6]), "+f"(d[7]), "+f"(d[8]), "+f"(d[9]), "+f"(d[10]), "+f"(d[11]), "+f"(d[12]), "+f"(d[13]), "+f"(d[14]), "+f"(d[15]), "+f"(d[16]), "+f"(d[17]), "+f"(d[18]), "+f"(d[19]), "+f"(d[20]), "+f"(d[21]), "+f"(d[22]), "+f"(d[23]), "+f"(d[24]), "+f"(d[25]), "+f"(d[26]), "+f"(d[27]), "+f"(d[28]), "+f"(d[29]), "+f"(d[30]), "+f"(d[31]), "+f"(d[32]), "+f"(d[33]), "+f"(d[34]), "+f"(d[35]), "+f"(d[36]), "+f"(d[37]), "+f"(d[38]), "+f"(d[39]), "+f"(d[40]), "+f"(d[41]), "+f"(d[42]), "+f"(d[43]), "+f"(d[44]), "+f"(d[45]), "+f"(d[46]), "+f"(d[47]), "+f"(d[48]), "+f"(d[49]), "+f"(d[50]), "+f"(d[51]), "+f"(d[52]), "+f"(d[53]), "+f"(d[54]), "+f"(d[55]), "+f"(d[56]), "+f"(d[57]), "+f"(d[58]), "+f"(d[59]), "+f"(d[60]), "+f"(d[61]), "+f"(d[62]), "+f"(d[63]), "+f"(d[64]), "+f"(d[65]), "+f"(d[66]), "+f"(d[67]), "+f"(d[68]), "+f"(d[69]), "+f"(d[70]), "+f"(d[71]), "+f"(d[72]), "+f"(d[73]), "+f"(d[74]), "+f"(d[75]), "+f"(d[76]), "+f"(d[77]), "+f"(d[78]), "+f"(d[79]), "+f"(d[80]), "+f"(d[81]), "+f"(d[82]), "+f"(d[83]), "+f"(d[84]), "+f"(d[85]), "+f"(d[86]), "+f"(d[87]), "+f"(d[88]), "+f"(d[89]), "+f"(d[90]), "+f"(d[91]), "+f"(d[92]), "+f"(d[93]), "+f"(d[94]), "+f"(d[95])
    : "l"(descA), "l"(descB), "r"(accum));
}
template <> __device__ __forceinline__ void wgmma_ss<184>(float* d, uint64_t descA, uint64_t descB, uint32_t accum) {
  asm volatile(
    "{\n.reg .pred p;\n"
    "setp.ne.b32 p, %94, 0;\n"
    "wgmma.mma_async.sync.aligned.m64n184k16.f32.bf16.bf16 "
    "{%0, %1, %2, %3, %4, %5, %6, %7, %8, %9, %10, %11, %12, %13, %14, %15, %16, %17, %18, %19, %20, %21, %22, %23, %24, %25, %26, %27, %28, %29, %30, %31, %32, %33, %34, %35, %36, %37, %38, %39, %40, %41, %42, %43, %44, %45, %46, %47, %48, %49, %50, %51, %52, %53, %54, %55, %56, %57, %58, %59, %60, %61, %62, %63, %64, %65, %66, %67, %68, %69, %70, %71, %72, %73, %74, %75, %76, %77, %78, %79, %80, %81, %82, %83, %84, %85, %86, %87, %88, %89, %90, %91}, "
    "%92, %93, p, 1, 1, 0, 0;\n"
    "}\n"
    : "+f"(d[0]), "+f"(d[1]), "+f"(d[2]), "+f"(d[3]), "+f"(d[4]), "+f"(d[5]), "+f"(d[6]), "+f"(d[7]), "+f"(d[8]), "+f"(d[9]), "+f"(d[10]), "+f"(d[11]), "+f"(d[12]), "+f"(d[13]), "+f"(d[14]), "+f"(d[15]), "+f"(d[16]), "+f"(d[17]), "+f"(d[18]), "+f"(d[19]), "+f"(d[20]), "+f"(d[21]), "+f"(d[22]), "+f"(d[23]), "+f"(d[24]), "+f"(d[25]), "+f"(d[26]), "+f"(d[27]), "+f"(d[28]), "+f"(d[29]), "+f"(d[30]), "+f"(d[31]), "+f"(d[32]), "+f"(d[33]), "+f"(d[34]), "+f"(d[35]), "+f"(d[36]), "+f"(d[37]), "+f"(d[38]), "+f"(d[39]), "+f"(d[40]), "+f"(d[41]), "+f"(d[42]), "+f"(d[43]), "+f"(d[44]), "+f"(d[45]), "+f"(d[46]), "+f"(d[47]), "+f"(d[48]), "+f"(d[49]), "+f"(d[50]), "+f"(d[51]), "+f"(d[52]), "+f"(d[53]), "+f"(d[54]), "+f"(d[55]), "+f"(d[56]), "+f"(d[57]), "+f"(d[58]), "+f"(d[59]), "+f"(d[60]), "+f"(d[61]), "+f"(d[62]), "+f"(d[63]), "+f"(d[64]), "+f"(d[65]), "+f"(d[66]), "+f"(d[67]), "+f"(d[68]), "+f"(d[69]), "+f"(d[70]), "+f"(d[71]), "+f"(d[72]), "+f"(d[73]), "+f"(d[74]), "+f"(d[75]), "+f"(d[76]), "+f"(d[77]), "+f"(d[78]), "+f"(d[79]), "+f"(d[80]), "+f"(d[81]), "+f"(d[82]), "+f"(d[83]), "+f"(d[84]), "+f"(d[85]), "+f"(d[86]), "+f"(d[87]), "+f"(d[88]), "+f"(d[89]), "+f"(d[90]), "+f"(d[91])
    : "l"(descA), "l"(descB), "r"(accum));
}

template <int N> struct IC { static constexpr int v = N; };

__device__ __forceinline__ void stmatrix_x4_t(uint32_t addr, uint32_t r0, uint32_t r1, uint32_t r2, uint32_t r3) {
  asm volatile("stmatrix.sync.aligned.m8n8.x4.trans.shared.b16 [%0], {%1, %2, %3, %4};"
               ::"r"(addr), "r"(r0), "r"(r1), "r"(r2), "r"(r3) : "memory");
}
__device__ __forceinline__ void ldmatrix_x4(uint32_t* r, uint32_t addr) {
  asm volatile("ldmatrix.sync.aligned.m8n8.x4.shared.b16 {%0, %1, %2, %3}, [%4];"
               : "=r"(r[0]), "=r"(r[1]), "=r"(r[2]), "=r"(r[3]) : "r"(addr) : "memory");
}
__device__ __forceinline__ uint32_t pack_bf16(float a, float b) {
  __nv_bfloat162 v = __floats2bfloat162_rn(a, b);
  return *reinterpret_cast<uint32_t*>(&v);
}
__device__ __forceinline__ uint32_t prmt(uint32_t a, uint32_t b, uint32_t s) {
  uint32_t d;
  asm("prmt.b32 %0, %1, %2, %3;" : "=r"(d) : "r"(a), "r"(b), "r"(s));
  return d;
}
__device__ __forceinline__ uint32_t lds32(uint32_t a) {
  uint32_t v;
  asm volatile("ld.shared.u32 %0, [%1];" : "=r"(v) : "r"(a) : "memory");
  return v;
}
__device__ __forceinline__ void lds128(uint32_t* v, uint32_t a) {
  asm volatile("ld.shared.v4.u32 {%0, %1, %2, %3}, [%4];" : "=r"(v[0]), "=r"(v[1]), "=r"(v[2]), "=r"(v[3]) : "r"(a) : "memory");
}
__device__ __forceinline__ void sts128(uint32_t a, const uint32_t* v) {
  asm volatile("st.shared.v4.u32 [%0], {%1, %2, %3, %4};" ::"r"(a), "r"(v[0]), "r"(v[1]), "r"(v[2]), "r"(v[3]) : "memory");
}
__device__ __forceinline__ void sts32(uint32_t a, uint32_t v) {
  asm volatile("st.shared.u32 [%0], %1;" ::"r"(a), "r"(v) : "memory");
}
__device__ __forceinline__ void wait_until(uint32_t t0, uint32_t at) {
  asm volatile(
      "{\n.reg .pred p;\n.reg .s32 r;\n"
      "SPIN:\n"
      "mov.u32 r, %%clock;\n"
      "sub.s32 r, %0, r;\n"
      "setp.gt.s32 p, r, 0;\n"
      "shr.s32 r, r, %1;\n"
      "@p nanosleep.u32 r;\n"
      "@p bra.uni SPIN;\n}\n"
      ::"r"(t0 + at), "n"(NSH) : "memory");
}
__device__ __forceinline__ void spin_until(uint32_t t0, uint32_t at) {
  while ((uint32_t)clock() - t0 < at) {}
}
__device__ __forceinline__ void wait_count(const unsigned int* f, uint32_t& c) {
  asm volatile(
      "{\n.reg .pred p;\n.reg .u32 v;\n"
      "SPIN:\n"
      "ld.acquire.gpu.global.u32 v, [%1];\n"
      "add.u32 %0, %0, 16;\n"
      "setp.lt.u32 p, %0, 0x100000;\n"
      "setp.lt.and.u32 p, v, 64, p;\n"
      "@p nanosleep.u32 100;\n"
      "@p bra.uni SPIN;\n}\n"
      : "+r"(c) : "l"(f) : "memory");
}
template <int E>
__device__ __forceinline__ void ld_lut(uint32_t* v, const __nv_bfloat16* p) {
  asm volatile("ld.global.nc.u32 %0, [%1+%2];" : "=r"(v[E]) : "l"(p), "n"(((E & 3) * N_ + 8 * (E >> 2)) * 2));
  if constexpr (E < 7) ld_lut<E + 1>(v, p);
}
template <int OFF, int AL>
__device__ __forceinline__ void ld_codes4(uint32_t* w, const int* p) {
  if (AL) asm volatile("ld.global.nc.v4.u32 {%0, %1, %2, %3}, [%4+%5];" : "=r"(w[0]), "=r"(w[1]), "=r"(w[2]), "=r"(w[3]) : "l"(p), "n"(OFF));
  else asm volatile("ld.global.nc.L1::no_allocate.v4.u32 {%0, %1, %2, %3}, [%4+%5];" : "=r"(w[0]), "=r"(w[1]), "=r"(w[2]), "=r"(w[3]) : "l"(p), "n"(OFF));
}
template <int AL = SAL>
__device__ __forceinline__ void ld_codes(uint32_t* w, const int* p) {
  ld_codes4<0, AL>(w, p);
  ld_codes4<N_ * 4, AL>(w + 4, p);
  ld_codes4<N_ * 32, AL>(w + 8, p);
  ld_codes4<N_ * 36, AL>(w + 12, p);
}
__device__ __forceinline__ void prefetch_map(const CUtensorMap* map) {
  asm volatile("prefetch.tensormap [%0];" ::"l"((uint64_t)map) : "memory");
}
template <int OFF>
__device__ __forceinline__ void ld_words(uint32_t* w, const uint8_t* p) {
  asm volatile("ld.relaxed.gpu.global.v4.u32 {%0, %1, %2, %3}, [%4+%5];" : "=r"(w[0]), "=r"(w[1]), "=r"(w[2]), "=r"(w[3]) : "l"(p), "n"(OFF) : "memory");
}
template <int OFF>
__device__ __forceinline__ void st_words(uint8_t* p, const uint32_t* w) {
  asm volatile("st.relaxed.gpu.global.v4.u32 [%0+%5], {%1, %2, %3, %4};" ::"l"(p), "r"(w[0]), "r"(w[1]), "r"(w[2]), "r"(w[3]), "n"(OFF) : "memory");
}

#define DBG(i)

__device__ __forceinline__ uint32_t make_word(uint32_t c0, uint32_t c1, uint32_t c2, uint32_t c3, uint32_t odd) {
  const uint32_t m1 = odd ? 256u : 1u, m2 = 257u - m1, pat = odd ? 0x10320000u : 0x32100000u;
  uint32_t p01, p23, a, t1, t2;
  asm("mad.lo.u32 %0, %1, 16, %2;" : "=r"(p01) : "r"(c1), "r"(c0));
  asm("mad.lo.u32 %0, %1, 16, %2;" : "=r"(p23) : "r"(c3), "r"(c2));
  asm("mad.lo.u32 %0, %1, %2, %3;" : "=r"(a) : "r"(p23), "r"(m2), "r"(pat));
  asm("mad.lo.u32 %0, %1, %2, %3;" : "=r"(t1) : "r"(p01), "r"(m1), "r"(a));
  asm("mul.lo.u32 %0, %1, 0x800000;" : "=r"(a) : "r"(p23));
  asm("mad.lo.u32 %0, %1, 0x8000, %2;" : "=r"(t2) : "r"(p01), "r"(a));
  return (t1 | t2) & (0x44447777u | pat);
}
struct Planes { uint32_t v[4][4]; };
__device__ __forceinline__ void lookup4(const Planes& pl, int c, uint32_t s, uint32_t& o0, uint32_t& o1) {
  uint32_t s2;
  asm("{\n.reg .b16 l, h;\n.reg .b32 t;\nmov.b32 {l, h}, %1;\nmov.b32 t, {h, h};\nmul.rn.f16x2 %0, t, %2;\n}\n" : "=r"(s2) : "r"(s), "r"(0x3c003c00u));
  const uint32_t lo = prmt(prmt(pl.v[0][2 * c], pl.v[1][2 * c], s), prmt(pl.v[2][2 * c], pl.v[3][2 * c], s), s2);
  const uint32_t hi = prmt(prmt(pl.v[0][2 * c + 1], pl.v[1][2 * c + 1], s), prmt(pl.v[2][2 * c + 1], pl.v[3][2 * c + 1], s), s2);
  o0 = prmt(lo, hi, 0x5140);
  o1 = prmt(lo, hi, 0x7362);
}
__device__ __forceinline__ void store_planes(uint32_t dst, const uint32_t* lv) {
#pragma unroll
  for (int h = 0; h < 2; h++) {
    uint32_t qp[4];
#pragma unroll
    for (int c = 0; c < 2; c++) {
      const uint32_t a = prmt(lv[4 * c], lv[4 * c + 1], h ? 0x7362 : 0x5140), b = prmt(lv[4 * c + 2], lv[4 * c + 3], h ? 0x7362 : 0x5140);
      qp[2 * c] = prmt(a, b, 0x5410);
      qp[2 * c + 1] = prmt(a, b, 0x7632);
    }
    sts128(dst + 64 * h, qp);
  }
}
__device__ __forceinline__ bool words_ok(const uint32_t* P, uint32_t tag) {
  if (CK2) return (P[0] & P[4] & tag) != 0;
  return (P[0] & P[1] & P[2] & P[3] & P[4] & P[5] & P[6] & P[7] & tag) != 0;
}
template <int NJ>
__device__ __forceinline__ void stage_part(const float* a, uint32_t sts) {
#pragma unroll
  for (int j = 0; j < NJ; j++)
    stmatrix_x4_t(sts + 16 * j * 128, pack_bf16(a[8 * j], a[8 * j + 1]), pack_bf16(a[8 * j + 2], a[8 * j + 3]),
                  pack_bf16(a[8 * j + 4], a[8 * j + 5]), pack_bf16(a[8 * j + 6], a[8 * j + 7]));
}

template <int OFF>
__device__ __forceinline__ uint32_t lut_at(uint32_t tab, uint32_t c) {
  uint32_t v;
  asm volatile("ld.shared.u16 %0, [%1+%2];" : "=r"(v) : "r"(tab + 40 * c), "n"(OFF));
  return v;
}
template <int J>
__device__ __forceinline__ void convert_col(const uint32_t (*v)[4], uint32_t tab, uint8_t* dst) {
  uint32_t o[4];
#pragma unroll
  for (int i = 0; i < 4; i++) {
    const uint32_t a = lut_at<2 * J>(tab, v[2 * i][J]), b = lut_at<2 * J>(tab, v[2 * i + 1][J]);
    asm("mad.lo.u32 %0, %1, 65536, %2;" : "=r"(o[i]) : "r"(b), "r"(a));
  }
  st_words<2048 * J>(dst, o);
}

struct Maps { CUtensorMap m[NMAPS]; uint64_t desc; uint32_t tiles[66]; };
#define TILES() \
  const int fta = (te & 15) + rank, ftb = ((te >> 4) & 15) + rank, toka = (te >> 8) & 0xfff, tokb = te >> 20; \
  const bool big = fta < 12; \
  (void)toka; (void)big; (void)tokb
__global__ void __cluster_dims__(2, 1, 1) __launch_bounds__(NTHREADS, 1)
fused_kernel(unsigned int* __restrict__ count, const __nv_bfloat16* __restrict__ lut, uint8_t* __restrict__ gp,
             const int* __restrict__ qw, const uint8_t* __restrict__ xg, const __grid_constant__ Maps maps) {
  extern __shared__ __align__(1024) uint8_t smem_gen[];
  const uint32_t t0 = clock();
  const int tid = threadIdx.x;
  uint32_t cf[16];
  const int* src = qw + (((tid >> 8) * BK + 32 + (tid & 48) + ((tid >> 1) & 6)) * N_ + (blockIdx.x & 127) * 16 + (tid & 3) * 4);
  if ((tid >> 6) == 2) ld_codes(cf, src);
  const uint32_t te = maps.tiles[blockIdx.x >> 1];
  const int rank = blockIdx.x & 1;
  const uint32_t sl = smem_u32(smem_gen);
  auto bar = [&](int i) { return sl + OFF_BAR + 8 * i; };
  const int w12 = __shfl_sync(0xffffffffu, tid >> 5, 0);
  const int wg = w12 >> 2;
  const int warp = w12 & 3;
  const int lane = tid & 31;
  uint32_t bud = 0;
  if (__builtin_expect(wg == 0, 1)) {
    asm volatile("setmaxnreg.dec.sync.aligned.u32 72;");
    if (warp == 0) {
      if (lane == 0) {
#pragma unroll
        for (int i = 0; i < NBARS; i++) mbar_init(bar(i), i >= 4 && i < 8 ? 4 : 1);
        mbar_init(bar(B_LAST), 4);
        asm volatile("fence.mbarrier_init.release.cluster;" ::: "memory");
      }
      __syncwarp();
      cluster_arrive_relaxed();
      asm volatile("bar.arrive 4, 128;" ::: "memory");
      DBG(1);
      TILES();
      expect_w(bar(B_DIR), 2 * UNIT_BYTES);
      tma3_w(sl + 3 * STAGE_BYTES, &maps.m[M_D], bar(B_DIR), 0, 0, fta * 4);
      expect_w(bar(B_FULL), X_BYTES);
      cluster_wait();
      tma_mc_w(sl + rank * (X_BYTES / 2), &maps.m[M_XA], bar(B_FULL), 0, toka + rank * (TA / 2));
      DBG(2);
      expect_w(bar(B_LAST), SLAB_BYTES);
      wait_until(t0, XT0);
#pragma unroll 1
      for (int n = 1; n < 2 * KBLKS - 3; n++) {
        const int stage = n & 3;
        const bool first = n < KBLKS;
        const int rows = rank * (first ? TA / 2 : TB / 2);
        mbar_wait(bar(B_EMPTY + stage), ((n - 3) >> 2) & 1, bud);
        expect_w(bar(B_FULL + stage), STAGE_BYTES);
        tma_mc_w(sl + stage * STAGE_BYTES + rows * 128, &maps.m[first ? M_XA : M_XB], bar(B_FULL + stage),
                 (n & (KBLKS - 1)) * BK, (first ? toka : tokb) + rows);
        if (n <= KBLKS) {
          wait_until(t0, WT0 + min(n - 1, NWG) * WTS);
          bulk_w(sl + ((n - 1) & 3) * STAGE_BYTES + X_BYTES, gp + (fta * KBLKS + n - 1) * SLAB_BYTES, SLAB_BYTES, bar(B_FULL + (n & 19)));
        }
        if (n == PN) wait_count(count + 32 * (1 + ((lds32(sl + OFF_EPOCH) & 256) ? 48 : 0) + 4 * ftb), bud);
        if (first) continue;
        if (n == KBLKS + 4 || n == KBLKS + 8) asm volatile("bar.sync %0, 64;" ::"r"(n & 8) : "memory");
        tma_w(sl + stage * STAGE_BYTES + TB * 128, &maps.m[M_W], bar(B_FULL + stage), (n - KBLKS) * BK, ftb * BF);
        tma_w(sl + stage * STAGE_BYTES + TB * 128 + 8192, &maps.m[M_W], bar(B_FULL + stage), (n - KBLKS) * BK, ftb * BF + 64);
      }
      const uint32_t s1 = sl + STAGE_BYTES, s2 = s1 + STAGE_BYTES, s3 = s2 + STAGE_BYTES;
      const CUtensorMap *mx = &maps.m[M_XB], *mw = &maps.m[M_W];
      DBG(220);
      mbar_wait(bar(B_EMPTY + 1), 0, bud);
      DBG(221);
      expect_w(bar(B_FULL + 1), STAGE_BYTES);
      tma_mc_w(s1 + rank * 12288, mx, bar(B_FULL + 1), (13 + rank) * BK, tokb);
      tma_w(s1 + 24576, mw, bar(B_FULL + 1), 13 * BK, ftb * BF);
      tma_w(s1 + 32768, mw, bar(B_FULL + 1), 14 * BK, ftb * BF);
      DBG(222);
      mbar_wait(bar(B_EMPTY + 2), 0, bud);
      DBG(223);
      asm volatile("bar.sync 15, 96;" ::: "memory");
      DBG(224);
      expect_w(bar(B_FULL + 2), 20480);
      if (!rank) tma_mc_w(s2, mx, bar(B_FULL + 2), 15 * BK, tokb);
      tma_w(s2 + 12288, mw, bar(B_FULL + 2), 15 * BK, ftb * BF);
      DBG(225);
      expect_w(bar(B_RDY), 24576);
      tma_w(s2 + 20480, mw, bar(B_RDY), 13 * BK, ftb * BF + 64);
      tma_w(s2 + 28672, mw, bar(B_RDY), 14 * BK, ftb * BF + 64);
      tma_w(sl + OFF_STG + 24576, mw, bar(B_RDY), 15 * BK, ftb * BF + 64);
      DBG(226);
      mbar_wait(bar(B_EMPTY + 3), 1, bud);
      DBG(227);
      expect_w(bar(B_FULL + 3), 36864);
      tma_mc_w(s3 + rank * 12288, mx, bar(B_FULL + 3), (13 + rank) * BK, tokb + TB / 2);
      if (rank) tma_mc_w(s3 + 24576, mx, bar(B_FULL + 3), 15 * BK, tokb + TB / 2);
      asm volatile(ELECT "@p red.relaxed.gpu.global.add.u32 [%0], %1;\n}\n" ::"l"(count), "r"(blockIdx.x < 2 * NUM_CTAS - 256 ? 1 : 2) : "memory");
    } else {
      const int p = warp - 1;
      uint32_t ep;
      asm volatile("ld.relaxed.gpu.global.u32 %0, [%1];" : "=r"(ep) : "l"(count) : "memory");
      cluster_arrive_relaxed();
      prefetch_map(&maps.m[p]);
      asm volatile("prefetch.global.L2 [%0];" ::"l"(xg + (((blockIdx.x * 16 + p * 8 + (lane >> 2)) & (M_ - 1)) * (K_ * 2) + (lane & 3) * 32)));
      const uint32_t so = OFF_STG + p * UNIT_BYTES;
      const uint32_t ua = sl + so + (lane & 3) * 256 + (((lane >> 2) ^ (2 * (lane & 3))) << 4);
      asm volatile("bar.sync 4, 128;" ::: "memory");
      if (p == 2) {
        sts32(sl + OFF_EPOCH, ep);
        asm volatile("bar.arrive 1, 288;" ::: "memory");
      }
      int r = blockIdx.x, u = 128 + 3 * r + p;
      uint32_t ph = 0, odd;
#pragma unroll 1
      do {
        wait_until(t0, D0 + min(r * PER, R1 * (PER - PER2) + r * PER2));
        expect_w(bar(B_SLOT + p), UNIT_BYTES);
        tma_w(sl + so, &maps.m[M_Q], bar(B_SLOT + p), (u & 63) * 32, (u & ~63) + 32);
        DBG(16 + 8 * p + 2 * (r / NUM_CTAS));
        uint8_t* dst = gp + (((((u & 63) >> 2) * KBLKS + (u >> 6)) * 4 + (u & 3)) * 2048 + (lane >> 2) * 256 + (lane & 3) * 16);
        mbar_wait(bar(B_SLOT + p), ph, bud);
        asm volatile("and.b32 %0, %1, 256;" : "=r"(odd) : "r"(ep));
        DBG(184 + 4 * p + r / NUM_CTAS);
        uint32_t w[4][4];
#pragma unroll
        for (int b = 0; b < 4; b++) {
          uint32_t v[4][4];
          lds128(v[0], ua + b * 2048);
          lds128(v[1], (ua ^ 16) + b * 2048 + 128);
          lds128(v[2], ua + b * 2048 + 1024);
          lds128(v[3], (ua ^ 16) + b * 2048 + 1024 + 128);
#pragma unroll
          for (int j = 0; j < 4; j++) w[j][b] = make_word(v[0][j], v[1][j], v[2][j], v[3][j], odd);
        }
        st_words<0>(dst, w[0]); st_words<64>(dst, w[1]); st_words<128>(dst, w[2]); st_words<192>(dst, w[3]);
        __syncwarp();
        DBG(17 + 8 * p + 2 * (r / NUM_CTAS));
        ph ^= 1;
        r += NUM_CTAS;
        u += 3 * NUM_CTAS;
      } while (u < 1024);
      const int l = u - 1024, ls = (l * 1366) >> 16, cg = l - 48 * ls;
      unsigned int* cnt = count + (32 + 6 * __shfl_sync(0xffffffffu, odd, 0));
      prefetch_map(&maps.m[M_XB + p]);
      prefetch_map(&maps.m[M_Q2]);
      if (l < 384) {
        uint32_t e[8];
        const __nv_bfloat16* s = lut + ((lane & 15) * N_ + 2048 + cg * 32 + (lane & 16));
        asm volatile("ld.global.nc.v4.u32 {%0, %1, %2, %3}, [%4];" : "=r"(e[0]), "=r"(e[1]), "=r"(e[2]), "=r"(e[3]) : "l"(s));
        asm volatile("ld.global.nc.v4.u32 {%0, %1, %2, %3}, [%4+16];" : "=r"(e[4]), "=r"(e[5]), "=r"(e[6]), "=r"(e[7]) : "l"(s));
        wait_until(t0, LT0 + l * LTS);
        expect_w(bar(B_SLOT + p), 2 * UNIT_BYTES);
        tma3_w(sl + so, &maps.m[M_Q2], bar(B_SLOT + p), 2048 + cg * 32, ls * 16, 0);
        tma3_w(sl + so + 32768, &maps.m[M_Q2], bar(B_SLOT + p), 2048 + cg * 32, ls * 16, 4);
        DBG(22 + 8 * p);
        uint32_t tab = sl + OFF_TAB + p * 1536 + (lane >> 4) * 644;
#pragma unroll
        for (int i = 0; i < 8; i++) sts32(tab + (lane & 15) * 40 + 4 * i, e[i]);
        __syncwarp();
        uint8_t* dst = gp + (W_OFF + cg * 65536 + ls * 256 + (lane >> 4) * 32768 + (lane & 15) * 16);
        const uint32_t src = sl + so + (lane & 15) * 128 + ((((lane >> 2) & 4) ^ (lane & 7)) << 4);
        mbar_wait(bar(B_SLOT + p), ph, bud);
#pragma unroll 1
        for (int c = 0; c < 64; c += 16, tab += 8, dst += 8192) {
          uint32_t v[8][4];
#pragma unroll
          for (int i = 0; i < 8; i++) lds128(v[i], (src ^ c) + (i & 3) * 2048 + (i >> 2) * 32768);
          convert_col<0>(v, tab, dst);
          convert_col<1>(v, tab, dst);
          convert_col<2>(v, tab, dst);
          convert_col<3>(v, tab, dst);
        }
        __syncwarp();
        DBG(23 + 8 * p);
      }
      arrive_w(bar(B_LAST));
      if (l < 384)
        asm volatile(ELECT "@p fence.proxy.async.global;\n@p red.release.gpu.global.add.u32 [%0], %1;\n}\n"
                     ::"l"(cnt + 32 * ((cg & ~3) + min(ls >> 1, 2))), "r"(ls < 4 ? 8 : 4) : "memory");
      cluster_wait();
      TILES();
      if (p > 0) {
        asm volatile("bar.sync %0, 160;" ::"r"(12 + p) : "memory");
        if (FEN) asm volatile("fence.proxy.async.shared::cta;" ::: "memory");
        uint32_t t1 = clock();
#pragma unroll 1
        for (int i = 0; i < TA; i += OB, t1 += PC * OB / 32) {
          wait_until(t1, 0);
          const int rr = min(i, (big ? TA : TC) - OB);
          store_w(&maps.m[M_O32], sl + OFF_STG + (p - 1) * 32768 + rr * 128, fta * BF + 64 * (p - 1), toka + rr);
        }
        bulk_wait_read();
        DBG(227 + p);
        asm volatile("bar.arrive 15, 96;" ::: "memory");
      } else {
        prefetch_map(&maps.m[M_W]);
        if (blockIdx.x < 48) count[32 * (50 + blockIdx.x) - (cnt - count)] = 0;
#pragma unroll 1
        for (int i = 1; i < 3; i++) {
          wait_count(cnt + 32 * (4 * ftb + i), bud);
          asm volatile("bar.arrive %0, 64;" ::"r"(8 * i - 8) : "memory");
        }
      }
    }
    asm volatile("exit;");
  }
  const int cw = wg - 1;
  TILES();
  cluster_arrive_relaxed();
  if (warp >= 2)
    ld_lut<0>(cf, lut + (fta * BF + 4 * (lane & 3) * N_ + 64 * cw + 32 * (warp & 1) + (lane & 16) + ((lane >> 1) & 6)));
  else if (cw) {
    spin_until(t0, S1D);
    ld_codes(cf, src);
  }
  asm volatile("bar.sync 1, 288;" ::: "memory");
  const uint32_t odd = lds32(sl + OFF_EPOCH) & 256;
  DBG(40 + w12);
  if (warp >= 2) store_planes(sl + OFF_PL + cw * 32768 + (warp & 1) * 1024 + (lane & 28) * 32 + (lane & 3) * 16, cf);
  else {
    uint8_t* dst = gp + (((blockIdx.x & 120) * 2 + cw) * SLAB_BYTES + (blockIdx.x & 7) * 1024 + (tid & 63) * 16);
    const uint32_t tb = sl + OFF_STG + 61440 + cw * 1024;
#pragma unroll
    for (int j = 0; j < 4; j++)
      sts32(tb + (lane & 3) * 256 + j * 64 + (lane & 12) * 4 + ((tid >> 2) & 12), make_word(cf[j], cf[4 + j], cf[8 + j], cf[12 + j], odd));
    asm volatile("bar.sync %0, 64;" ::"r"(6 + cw) : "memory");
    lds128(cf, tb + (tid & 63) * 16);
    st_words<0>(dst, cf);
  }
  DBG(52 + w12);
  asm volatile("setmaxnreg.inc.sync.aligned.u32 216;");
  uint32_t rel = (tid & 127) < 2 ? mapa(bar(B_EMPTY), lane) : 0u;
  uint32_t tg = (w12 - 4) * 1024 + lane * 16;
  uint32_t tw = sl + X_BYTES + tg;
  const uint8_t* gt = gp + (tg + fta * KBLKS * SLAB_BYTES);
  uint32_t tag = odd ? (1u << 17) : (1u << 25);
  asm volatile("" : "+r"(tw), "+l"(gt), "+r"(rel), "+r"(tag));
  Planes pl;
  uint32_t A[16], P[8];
  float acc[TA / 2];
  DBG(64 + cw);
  {
    const uint32_t td = sl + 3 * STAGE_BYTES - 8192 + (w12 >> 1) * 4096 + (lane & 3) * 256 + ((((tid >> 3) & 4) ^ (lane >> 4) ^ (2 * (lane & 3))) << 4) + (lane & 12);
    mbar_wait(bar(B_DIR), 0, bud);
    DBG(88 + cw);
#pragma unroll
    for (int k = 0; k < 4; k++) {
      const uint32_t a = (td ^ ((k & 2) << 4)) + (k & 1) * 2048;
      P[2 + (k & 1) + 2 * (k & 2)] = make_word(lds32(a), lds32((a ^ 16) + 128), lds32(a + 1024), lds32((a ^ 16) + 1152), 0);
    }
  }
  asm volatile("bar.sync %0, 128;" ::"r"(2 + cw) : "memory");
#pragma unroll
  for (int k = 0; k < 4; k++) lds128(pl.v[k], sl + OFF_PL + cw * 32768 + (tid & 124) * 16 + 16 * k);
  mbar_wait(bar(B_FULL), 0, bud);
  DBG(66 + cw);
  auto tile1 = [&](auto nh) {
    uint32_t d = UD, dn, fb = bar(B_FULL + 1), pa = 0;
#pragma unroll 1
    for (int n = 0; n < KBLKS; n++) {
      bool ok;
#pragma unroll
      for (int b = 0; b < 4; b++) {
        const int m = n + 1;
        if (b == WB && !EP1) mbar_wait_fast(fb, (m >> 2) & 1, bud);
        if (b == WB && EP1 == 1 && !ok) mbar_wait(fb, (m >> 2) & 1, bud);
        if (b == 1 && EP1 == 3) ok = mbar_test(fb, (m >> 2) & 1);
        if (b == 2) {
#pragma unroll 1
          while (__builtin_expect(!words_ok(P, tag), 0)) {
            if ((bud += 16) >= 0x100000) break;
            asm volatile("{\n.reg .u64 a;\nmad.wide.u32 a, %8, 8192, %9;\nld.relaxed.gpu.global.v4.u32 {%0, %1, %2, %3}, [a];\n"
                         "ld.relaxed.gpu.global.v4.u32 {%4, %5, %6, %7}, [a+512];\n}\n"
                         : "=r"(P[0]), "=r"(P[1]), "=r"(P[2]), "=r"(P[3]), "=r"(P[4]), "=r"(P[5]), "=r"(P[6]), "=r"(P[7]) : "r"(n), "l"(gt) : "memory");
          }
          __syncwarp();
        }
        lookup4(pl, 0, P[b ^ 2], A[4 * b], A[4 * b + 2]);
        lookup4(pl, 1, P[4 + (b ^ 2)], A[4 * b + 1], A[4 * b + 3]);
        if (b == 1) {
          if (EP1 >= 2 && !ok) mbar_wait(fb, (m >> 2) & 1, bud);
          lds128(P, tw + pa);
          lds128(P + 4, tw + pa + 512);
        }
        if (b == 3) {
          asm volatile("mad.lo.u32 %0, %1, %3, %2;" : "=r"(dn) : "r"(m & 3), "r"(UD), "n"(STAGE_BYTES / 16));
          asm volatile("mad.lo.u32 %0, %1, 8, %2;" : "=r"(fb) : "r"((m + 1) & 19), "r"(bar(B_FULL)));
          asm volatile("mul.lo.u32 %0, %1, %2;" : "=r"(pa) : "r"(m & 3), "n"(STAGE_BYTES));
        }
        if (WAITS & (1 << ((b + 3) & 3))) wgmma_wait<1>();
        if (b == 1) mbar_arrive_remote_if(rel + 8 * ((n - 1) & 3), rel);
        if (b == S1B && n == S1N && cw == 1) asm volatile("bar.sync 9, 256;" ::: "memory");
        if (b == 0 && (EP1 == 1 || EP1 == 2)) ok = mbar_test(fb, (m >> 2) & 1);
        wgmma_fence();
        wgmma_rs<decltype(nh)::v>(acc + TB / 2, A + 4 * b, d + 2 * b + TB * 8, b > 0 || n != 0);
        wgmma_rs<TB>(acc, A + 4 * b, d + 2 * b, b > 0 || n != 0);
        wgmma_commit();
      }
      d = dn;
    }
  };
  if (big) tile1(IC<TA - TB>()); else tile1(IC<TC - TB>());
  if (cw != 1) asm volatile("bar.arrive 9, 256;" ::: "memory");
  const uint32_t stg = sl + OFF_STG + cw * 32768;
  const uint32_t so8 = stg + ((lane & 7) + ((lane >> 4) << 3)) * 128 + (((2 * warp + ((lane >> 3) & 1)) ^ (lane & 7)) << 4);
  DBG(212 + cw);
  mbar_wait(bar(B_FULL), 0, bud);
  DBG(214 + cw);
  if (NP > 1 && !W17) mbar_wait(bar(B_FULL + 1), 0, bud);
  DBG(216 + cw);
  const uint64_t ub = maps.desc, ua = ub + (TB * 8 + cw * 512);
  wgmma_wait<0>();
  mbar_arrive_remote_if(rel + 24, rel);
  fence_regs(acc);
  DBG(68 + cw);
  {
    uint32_t o[64];
#pragma unroll
    for (int k = 0; k < 48; k++) o[k] = pack_bf16(acc[2 * k], acc[2 * k + 1]);
#pragma unroll
    for (int k = 0; k < 48; k++) asm volatile("" : "+r"(o[k]) :: "memory");
    DBG(92 + cw);
    wgmma_fence();
#pragma unroll
    for (int b = 0; b < 4 * NP; b++) {
      const int so = (b >> 2) * (STAGE_BYTES / 16) + 2 * (b & 3);
      if (b == 4 && W17) mbar_wait(bar(B_FULL + 1), 0, bud);
      wgmma_ss<TB>(acc, ua + so, ub + so, b != 0);
      if ((b & 3) == 3 || b == 4) wgmma_commit();
      if (b == 0) {
#pragma unroll
        for (int k = 48; k < 64; k++) o[k] = pack_bf16(acc[2 * k], acc[2 * k + 1]);
      }
      if (b == 4) {
        wgmma_wait<1>();
        mbar_arrive_remote_if(rel, rel);
      }
#pragma unroll
      for (int j = 0; j < 16; j++)
        if (j * NSB / 16 + SB0 == b) stmatrix_x4_t(so8 + j * 2048, o[4 * j], o[4 * j + 1], o[4 * j + 2], o[4 * j + 3]);
    }
  }
  if (!FEN) asm volatile("fence.proxy.async.shared::cta;" ::: "memory");
  asm volatile("bar.arrive %0, 160;" ::"r"(13 + cw) : "memory");
  cluster_wait();
  DBG(70 + cw);
  auto tile2 = [&](auto nt) {
#pragma unroll 1
    for (int n = NP; n < KBLKS - 3; n++) {
      const uint32_t so = (n & 3) * (STAGE_BYTES / 16);
      mbar_wait_fast(bar(B_FULL) + 8 * (n & 3), (n >> 2) & 1, bud);
      wgmma_fence();
      wgmma_ss<decltype(nt)::v>(acc, ua + so, ub + so, 1);
      wgmma_commit();
      wgmma_wait<1>();
      mbar_arrive_remote_if(rel + 8 * ((n - 1) & 3), rel);
#pragma unroll
      for (int b = 1; b < 4; b++) wgmma_ss<decltype(nt)::v>(acc, ua + so + 2 * b, ub + so + 2 * b, 1);
      wgmma_commit();
    }
  };
  if (big) tile2(IC<TD>()); else tile2(IC<TB>());
  uint32_t W[48];
  float c2[TB / 2];
  DBG(72 + cw);
  const uint32_t wa = sl + (warp * 16 + (lane & 15)) * 128 + (((lane >> 4) ^ (lane & 7)) << 4);
  const uint32_t w0 = wa + (cw ? 2 * STAGE_BYTES + 20480 : STAGE_BYTES + 24576), w2 = wa + (cw ? OFF_STG + 24576 : 2 * STAGE_BYTES + 12288);
  mbar_wait(bar(B_FULL + 1), 1, bud);
  mbar_wait(bar(cw ? B_RDY : UPF == 2 ? B_FULL + 2 : B_FULL + 1), 1, bud);
#pragma unroll
  for (int b = 0; b < 8; b++) ldmatrix_x4(W + 4 * b, (w0 ^ ((b & 3) << 5)) + (b >> 2) * 8192);
  if (UPF) {
    if (UPF == 1) mbar_wait(bar(B_FULL + 2), 1, bud);
    DBG(218 + cw);
#pragma unroll
    for (int b = 0; b < 4; b++) ldmatrix_x4(W + 32 + 4 * b, w2 ^ (b << 5));
  }
  const uint64_t dl = ub + STAGE_BYTES / 16;
  wgmma_wait<0>();
#pragma unroll
  for (int k = 0; k < TB / 2; k++) asm volatile("mov.b32 %0, %1;" : "=f"(c2[k]) : "f"(acc[k]) : "memory");
#pragma unroll
  for (int h = 0; h < 2; h++) {
    if (h) mbar_wait(bar(B_FULL + 3), 1, bud);
    if (h || cw) asm volatile("bar.sync %0, 256;" ::"r"(9 + 2 * h + cw) : "memory");
    DBG(74 + 6 * h + cw);
    auto half = [&](auto nn) {
      bool ok = false;
      wgmma_fence();
#pragma unroll
      for (int i = 0; i < 12; i++) {
        if (!UPF && h == 0 && EP2 >= 0 && i == EP2) ok = mbar_test(bar(B_FULL + 2), 1);
        if (!UPF && h == 0 && i == MI) {
          if (!ok) mbar_wait(bar(B_FULL + 2), 1, bud);
#pragma unroll
          for (int b = 0; b < 4; b++) ldmatrix_x4(W + 32 + 4 * b, w2 ^ (b << 5));
        }
        if (!UPF && h == 0 && i == 8) wgmma_fence();
        const int off = (h ? 2 * STAGE_BYTES + (i >> 2) * 12288 : i < 8 ? (i >> 2) * 12288 : STAGE_BYTES) / 16 + 2 * (i & 3);
        if constexpr (decltype(nn)::v == 96) wgmma_rl<96>(c2 + 48 * h, W + 4 * i, dl + off);
        else wgmma_rs<decltype(nn)::v>(c2 + 48 * h, W + 4 * i, UD + STAGE_BYTES / 16 + off, 1);
        if (i == NSI - 1) wgmma_commit();
      }
      wgmma_commit();
    };
    if (N88 && h && big) half(IC<TD - TB / 2>()); else half(IC<TB / 2>());
    wgmma_wait<1>();
    if (!h || !cw) asm volatile("bar.arrive %0, 256;" ::"r"(10 + 2 * h + cw) : "memory");
    const int r2 = h ? (big ? TD - 96 : TB - 96) : 0;
    wgmma_wait<0>();
#pragma unroll
    for (int k = 0; k < 48; k++) asm volatile("" : "+f"(c2[48 * h + k]) :: "memory");
    DBG(76 + 6 * h + cw);
    stage_part<6>(c2 + 48 * h, so8 + 96 * 128 * h);
    asm volatile("fence.proxy.async.shared::cta;" ::: "memory");
    asm volatile("bar.sync %0, 128;" ::"r"(2 + cw) : "memory");
    if (O24) store_w(&maps.m[M_O96], stg + (r2 + 24 * warp) * 128, 2048 + ftb * BF + 64 * cw, tokb + r2 + 24 * warp);
    else if (warp == 0) store_w(&maps.m[M_O96], stg + r2 * 128, 2048 + ftb * BF + 64 * cw, tokb + r2);
    DBG(78 + 6 * h + cw);
  }
  bulk_wait_read();
}

typedef CUresult (*EncodeFn)(CUtensorMap*, CUtensorMapDataType, cuuint32_t, void*, const cuuint64_t*, const cuuint64_t*,
                             const cuuint32_t*, const cuuint32_t*, CUtensorMapInterleave, CUtensorMapSwizzle,
                             CUtensorMapL2promotion, CUtensorMapFloatOOBfill);

}

extern "C" void kernel_launch(void* const* d_in, const int* in_sizes, int n_in, void* d_out, int out_size) {
  const __nv_bfloat16* x = (const __nv_bfloat16*)d_in[0];
  const int* qw = (const int*)d_in[1];
  const __nv_bfloat16* lut = (const __nv_bfloat16*)d_in[2];

  static EncodeFn enc = nullptr;
  static unsigned int* count = nullptr;
  static uint8_t* gp = nullptr;
  if (!enc) {
    cudaDriverEntryPointQueryResult q;
    void* fn = nullptr;
    cudaGetDriverEntryPoint("cuTensorMapEncodeTiled", &fn, cudaEnableDefault, &q);
    enc = (EncodeFn)fn;
    cudaGetSymbolAddress((void**)&count, g_count);
    cudaGetSymbolAddress((void**)&gp, g_p);
    cudaFuncSetAttribute(fused_kernel, cudaFuncAttributeMaxDynamicSharedMemorySize, SMEM_BYTES);
  }
  Maps maps;
  const cuuint32_t es[3] = {1, 1, 1};
  auto map2 = [&](int i, CUtensorMapDataType t, const void* p, int d0, int d1, int bytes, int b0, int b1, CUtensorMapL2promotion pr) {
    cuuint64_t dims[2] = {(cuuint64_t)d0, (cuuint64_t)d1};
    cuuint64_t strides[1] = {(cuuint64_t)d0 * bytes};
    cuuint32_t box[2] = {(cuuint32_t)b0, (cuuint32_t)b1};
    enc(&maps.m[i], t, 2, (void*)p, dims, strides, box, es, CU_TENSOR_MAP_INTERLEAVE_NONE, CU_TENSOR_MAP_SWIZZLE_128B, pr, CU_TENSOR_MAP_FLOAT_OOB_FILL_NONE);
  };
  map2(M_XA, CU_TENSOR_MAP_DATA_TYPE_BFLOAT16, x, K_, M_, 2, BK, TA / 2, XPROM);
  map2(M_XB, CU_TENSOR_MAP_DATA_TYPE_BFLOAT16, x, K_, M_, 2, BK, TB / 2, XPROM);
  map2(M_O96, CU_TENSOR_MAP_DATA_TYPE_BFLOAT16, d_out, N_, M_, 2, 64, O24 ? 24 : 96, CU_TENSOR_MAP_L2_PROMOTION_NONE);
  map2(M_O32, CU_TENSOR_MAP_DATA_TYPE_BFLOAT16, d_out, N_, M_, 2, 64, OB, CU_TENSOR_MAP_L2_PROMOTION_NONE);
  map2(M_Q, CU_TENSOR_MAP_DATA_TYPE_INT32, qw, N_, K_, 4, 32, BK, QPROM);
  map2(M_W, CU_TENSOR_MAP_DATA_TYPE_BFLOAT16, gp + W_OFF, K_, N_ - 2048, 2, BK, 64, XPROM);
  {
    cuuint64_t dims[3] = {(cuuint64_t)N_, (cuuint64_t)K_ / 8, 8};
    cuuint64_t strides[2] = {(cuuint64_t)N_ * 32, (cuuint64_t)N_ * 4};
    cuuint32_t box[3] = {32, 16, 4};
    enc(&maps.m[M_Q2], CU_TENSOR_MAP_DATA_TYPE_INT32, 3, (void*)qw, dims, strides, box, es, CU_TENSOR_MAP_INTERLEAVE_NONE,
        CU_TENSOR_MAP_SWIZZLE_128B, QPROM, CU_TENSOR_MAP_FLOAT_OOB_FILL_NONE);
  }
  {
    cuuint64_t dims[3] = {32, (cuuint64_t)K_, (cuuint64_t)N_ / 32};
    cuuint64_t strides[2] = {(cuuint64_t)N_ * 4, 128};
    cuuint32_t box[3] = {32, 32, 4};
    enc(&maps.m[M_D], CU_TENSOR_MAP_DATA_TYPE_INT32, 3, (void*)qw, dims, strides, box, es, CU_TENSOR_MAP_INTERLEAVE_NONE,
        CU_TENSOR_MAP_SWIZZLE_128B, QPROM, CU_TENSOR_MAP_FLOAT_OOB_FILL_NONE);
  }
  maps.desc = (0x40000040ull << 32) + UD;
  for (int t = 0; t < 66; t++) {
    const int u = t - 32, g = t < 32 ? t & 7 : 1 + u % 7, j = t < 32 ? t >> 3 : 4 + u / 7;
    int cl = t >= 60 ? (int)((0x413B3F394035ull >> (8 * (t - 60))) & 0xff) : g == 7 ? 48 + 2 * j : g ? 6 * j + g - 1 : std::min(49 + 6 * j, 87 - 12 * j);
    if (GMAP == 0) cl = (t + 4) % 66;
    const int yi = cl / 6, fb = 2 * (cl % 6);
    const int fa = cl < 48 ? fb : 12 + 2 * (cl & 1), ta = cl < 48 ? TA * yi : std::min(TC * ((cl - 48) >> 1), M_ - TC);
    maps.tiles[t >= 62 ? t & 3 : t + 4] = fa | fb << 4 | ta << 8 | (TD * yi + (TB - TD) * std::max(yi - 8, 0)) << 20;
  }
  fused_kernel<<<NUM_CTAS, NTHREADS, SMEM_BYTES, cudaStreamPerThread>>>(count, lut, gp, qw, (const uint8_t*)x, maps);
}
```

```cpp
#include <cuda_runtime.h>
#include <cuda_bf16.h>
#include <cuda.h>
#include <stdint.h>
#include <cstdio>
#include <algorithm>

namespace {

constexpr int M_ = 2048, K_ = 1024, N_ = 3584;
constexpr int BF = 128, BK = 64;
constexpr int TA = 256, TB = 192;
#define TCC 232
constexpr int TC = TCC, TD = 184;
constexpr int STAGES = 4;
constexpr int KBLKS = K_ / BK;
constexpr int X_BYTES = TA * BK * 2;
constexpr int UNIT_BYTES = BK * 32 * 4;
constexpr int SLAB_BYTES = BF * BK;
constexpr int STAGE_BYTES = X_BYTES + SLAB_BYTES;
constexpr int OFF_STG = STAGES * STAGE_BYTES;
constexpr int OFF_PL = OFF_STG + 3 * UNIT_BYTES;
constexpr int OFF_TAB = OFF_PL + 2048;
constexpr int OFF_BAR = OFF_STG + 65536;
constexpr int W_OFF = 16 * KBLKS * SLAB_BYTES;
constexpr int SMEM_BYTES = OFF_BAR + 512;
constexpr int NUM_CTAS = 132;
constexpr int NTHREADS = 384;
constexpr int NPACK = 3;
#define XT0 1400
#define WT0 2350
#define WTS 1000
#define S1D 400
#define PC 900
#define OB 32
#define WD 0x2212
#define RB 1
#define D0 600
#define WB 1
#define LT0 7800
#define LTS 15
#define XPROM CU_TENSOR_MAP_L2_PROMOTION_L2_128B
#define QPROM CU_TENSOR_MAP_L2_PROMOTION_L2_128B
#define S1B 1
#define S1N 15
#define NP 2
#define PN 16
#define MI 6
#define EP1 1
#define EP2 4
#define UPF 0
#define W17 1
#define SB0 0
#define NSB 8
#define FEN 1
#define NSI 10
#define N88 1
#define GMAP 1
#define O24 1
#define EPW 1
#define LCAP 12300
#define NB3 1
#define T2L 1
#define ORD 1
#define PU 36
#define U0(r, p) (ORD == 0 ? 3 * (r) + (p) : ORD == 1 ? 132 * (p) + (r) : (p) ? 131 + 2 * (r) + (p) : (r))
#define G0 WT0
#define G1 (WT0 + WTS)
#define G2 (WT0 + 2 * WTS)
#define G3 (WT0 + 3 * WTS)
#define G4 (WT0 + 4 * WTS)
#define G5 (WT0 + 5 * WTS)
constexpr uint64_t GATES = (uint64_t)(G0 / 32) << 8 | (uint64_t)(G1 / 32) << 16 | (uint64_t)(G2 / 32) << 24 | (uint64_t)(G3 / 32) << 32 | (uint64_t)(G4 / 32) << 40 | (uint64_t)(G5 / 32) << 48;
#define TR1 1
#define TR2 1
#define SW 0
#define XPD 2
#define XPS 2
#define XPW 1
#define ONE 1
#define SHF 1
#define PLF 1
#define NSH 2
static_assert(SMEM_BYTES <= 232448, "smem");
static_assert(TB * 128 + 2 * SLAB_BYTES == STAGE_BYTES, "stage");
constexpr int B_FULL = 0, B_EMPTY = 4, B_DIR = 8, B_SLOT = 9, NBARS = 12, B_LAST = 16, B_RDY = B_DIR;
constexpr int OFF_EPOCH = OFF_BAR + 8 * NBARS;
constexpr uint32_t SB = 1024;
constexpr uint32_t UD = (SB >> 4) | (1u << 16);
enum { M_Q, M_D, M_XA, M_XC, M_XB, M_XD, M_O96, M_O32, M_W, M_Q2, NMAPS };

__device__ __align__(1024) uint8_t g_p[W_OFF + 12 * KBLKS * 2 * SLAB_BYTES];
__device__ __align__(128) unsigned int g_count[32 * 97];

__device__ __forceinline__ uint32_t smem_u32(const void* p) { return (uint32_t)__cvta_generic_to_shared(p); }
__device__ __forceinline__ void mbar_init(uint32_t bar, uint32_t cnt) {
  asm volatile("mbarrier.init.shared::cta.b64 [%0], %1;" ::"r"(bar), "r"(cnt) : "memory");
}
__device__ __forceinline__ void mbar_wait(uint32_t bar, uint32_t parity, uint32_t& c) {
  asm volatile(
      "{\n.reg .pred p;\n"
      "SPIN:\n"
      "mbarrier.try_wait.parity.shared::cta.b64 p, [%1], %2;\n"
      "add.u32 %0, %0, 1;\n"
      "setp.ge.or.u32 p, %0, 0x100000, p;\n"
      "@!p bra.uni SPIN;\n}\n"
      : "+r"(c) : "r"(bar), "r"(parity) : "memory");
}
__device__ __forceinline__ void mbar_wait_fast(uint32_t bar, uint32_t parity, uint32_t& c) {
  asm volatile(
      "{\n.reg .pred p;\n"
      "SPIN:\n"
      "mbarrier.try_wait.parity.shared::cta.b64 p, [%1], %2;\n"
      "@p bra.uni DONE;\n"
      "add.u32 %0, %0, 1;\n"
      "setp.lt.u32 p, %0, 0x100000;\n"
      "@p bra.uni SPIN;\n"
      "DONE:\n}\n"
      : "+r"(c) : "r"(bar), "r"(parity) : "memory");
}
__device__ __forceinline__ bool mbar_test(uint32_t bar, uint32_t parity) {
  uint32_t ok;
  asm volatile("{\n.reg .pred p;\nmbarrier.try_wait.parity.shared::cta.b64 p, [%1], %2;\nselp.u32 %0, 1, 0, p;\n}\n" : "=r"(ok) : "r"(bar), "r"(parity) : "memory");
  return ok != 0;
}
__device__ __forceinline__ bool mbar_peek(uint32_t bar, uint32_t parity) {
  uint32_t ok;
  asm volatile("{\n.reg .pred p;\nmbarrier.test_wait.parity.shared::cta.b64 p, [%1], %2;\nselp.u32 %0, 1, 0, p;\n}\n" : "=r"(ok) : "r"(bar), "r"(parity) : "memory");
  return ok != 0;
}
__device__ __forceinline__ void mbar_arrive(uint32_t bar) {
  asm volatile("mbarrier.arrive.shared::cta.b64 _, [%0];" ::"r"(bar) : "memory");
}
__device__ __forceinline__ uint32_t mapa(uint32_t a, uint32_t cta) {
  uint32_t r;
  asm("mapa.shared::cluster.u32 %0, %1, %2;" : "=r"(r) : "r"(a), "r"(cta));
  return r;
}
__device__ __forceinline__ void mbar_arrive_remote_if(uint32_t ra, uint32_t cond) {
  asm volatile("{\n.reg .pred p;\nsetp.ne.u32 p, %1, 0;\n@p mbarrier.arrive.shared::cluster.b64 _, [%0];\n}\n" ::"r"(ra), "r"(cond) : "memory");
}
#define ELECT "{\n.reg .pred p;\nelect.sync _|p, 0xffffffff;\n"
__device__ __forceinline__ void expect_w(uint32_t bar, uint32_t bytes) {
  asm volatile(ELECT "@p mbarrier.arrive.expect_tx.shared::cta.b64 _, [%0], %1;\n}\n" ::"r"(bar), "r"(bytes) : "memory");
}
__device__ __forceinline__ void arrive_w(uint32_t bar) {
  asm volatile(ELECT "@p mbarrier.arrive.shared::cta.b64 _, [%0];\n}\n" ::"r"(bar) : "memory");
}
__device__ __forceinline__ void tma_mc_w(uint32_t dst, const CUtensorMap* map, uint32_t bar, int c0, int c1) {
  asm volatile(
      ELECT "@p cp.async.bulk.tensor.2d.shared::cluster.global.mbarrier::complete_tx::bytes.multicast::cluster [%0], [%1, {%3, %4}], [%2], %5;\n}\n"
      ::"r"(dst), "l"((uint64_t)map), "r"(bar), "r"(c0), "r"(c1), "h"((uint16_t)3) : "memory");
}
__device__ __forceinline__ void bulk_w(uint32_t dst, const void* src, uint32_t bytes, uint32_t bar) {
  asm volatile(ELECT "@p cp.async.bulk.shared::cluster.global.mbarrier::complete_tx::bytes [%0], [%1], %2, [%3];\n}\n"
               ::"r"(dst), "l"(src), "r"(bytes), "r"(bar) : "memory");
}
__device__ __forceinline__ void tma_w(uint32_t dst, const CUtensorMap* map, uint32_t bar, int c0, int c1) {
  asm volatile(
      ELECT "@p cp.async.bulk.tensor.2d.shared::cluster.global.mbarrier::complete_tx::bytes [%0], [%1, {%3, %4}], [%2];\n}\n"
      ::"r"(dst), "l"((uint64_t)map), "r"(bar), "r"(c0), "r"(c1) : "memory");
}
__device__ __forceinline__ void tma3_w(uint32_t dst, const CUtensorMap* map, uint32_t bar, int c0, int c1, int c2) {
  asm volatile(
      ELECT "@p cp.async.bulk.tensor.3d.shared::cluster.global.mbarrier::complete_tx::bytes [%0], [%1, {%3, %4, %5}], [%2];\n}\n"
      ::"r"(dst), "l"((uint64_t)map), "r"(bar), "r"(c0), "r"(c1), "r"(c2) : "memory");
}
__device__ __forceinline__ void store_w(const CUtensorMap* map, uint32_t src, int c0, int c1) {
  asm volatile(ELECT "@p cp.async.bulk.tensor.2d.global.shared::cta.bulk_group [%0, {%2, %3}], [%1];\n}\n"
               "cp.async.bulk.commit_group;"
               ::"l"((uint64_t)map), "r"(src), "r"(c0), "r"(c1) : "memory");
}
__device__ __forceinline__ void bulk_wait_read() { asm volatile("cp.async.bulk.wait_group.read 0;" ::: "memory"); }
__device__ __forceinline__ void cluster_arrive_relaxed() { asm volatile("barrier.cluster.arrive.relaxed.aligned;" ::: "memory"); }
__device__ __forceinline__ void cluster_wait() { asm volatile("barrier.cluster.wait.acquire.aligned;" ::: "memory"); }
__device__ __forceinline__ void wgmma_fence() { asm volatile("wgmma.fence.sync.aligned;" ::: "memory"); }
__device__ __forceinline__ void wgmma_commit() { asm volatile("wgmma.commit_group.sync.aligned;" ::: "memory"); }
template <int N> __device__ __forceinline__ void wgmma_wait() { asm volatile("wgmma.wait_group.sync.aligned %0;" ::"n"(N) : "memory"); }
template <int N> __device__ __forceinline__ void fence_regs(float (&p)[N]) {
#pragma unroll
  for (int i = 0; i < N; i++) asm volatile("" : "+f"(p[i]) :: "memory");
}

template <int N> __device__ __forceinline__ void wgmma_rs(float* d, const uint32_t* a, uint32_t descB, uint32_t accum);
template <> __device__ __forceinline__ void wgmma_rs<256>(float* d, const uint32_t* a, uint32_t descB, uint32_t accum) {
  asm volatile(
    "{\n.reg .pred p;\n.reg .b64 db;\n"
    "setp.ne.b32 p, %133, 0;\n"
    "mov.b64 db, {%132, 0x40000040};\n"
    "wgmma.mma_async.sync.aligned.m64n256k16.f32.bf16.bf16 "
    "{%0, %1, %2, %3, %4, %5, %6, %7, %8, %9, %10, %11, %12, %13, %14, %15, %16, %17, %18, %19, %20, %21, %22, %23, %24, %25, %26, %27, %28, %29, %30, %31, %32, %33, %34, %35, %36, %37, %38, %39, %40, %41, %42, %43, %44, %45, %46, %47, %48, %49, %50, %51, %52, %53, %54, %55, %56, %57, %58, %59, %60, %61, %62, %63, %64, %65, %66, %67, %68, %69, %70, %71, %72, %73, %74, %75, %76, %77, %78, %79, %80, %81, %82, %83, %84, %85, %86, %87, %88, %89, %90, %91, %92, %93, %94, %95, %96, %97, %98, %99, %100, %101, %102, %103, %104, %105, %106, %107, %108, %109, %110, %111, %112, %113, %114, %115, %116, %117, %118, %119, %120, %121, %122, %123, %124, %125, %126, %127}, "
    "{%128, %129, %130, %131}, db, p, 1, 1, 0;\n"
    "}\n"
    : "+f"(d[0]), "+f"(d[1]), "+f"(d[2]), "+f"(d[3]), "+f"(d[4]), "+f"(d[5]), "+f"(d[6]), "+f"(d[7]), "+f"(d[8]), "+f"(d[9]), "+f"(d[10]), "+f"(d[11]), "+f"(d[12]), "+f"(d[13]), "+f"(d[14]), "+f"(d[15]), "+f"(d[16]), "+f"(d[17]), "+f"(d[18]), "+f"(d[19]), "+f"(d[20]), "+f"(d[21]), "+f"(d[22]), "+f"(d[23]), "+f"(d[24]), "+f"(d[25]), "+f"(d[26]), "+f"(d[27]), "+f"(d[28]), "+f"(d[29]), "+f"(d[30]), "+f"(d[31]), "+f"(d[32]), "+f"(d[33]), "+f"(d[34]), "+f"(d[35]), "+f"(d[36]), "+f"(d[37]), "+f"(d[38]), "+f"(d[39]), "+f"(d[40]), "+f"(d[41]), "+f"(d[42]), "+f"(d[43]), "+f"(d[44]), "+f"(d[45]), "+f"(d[46]), "+f"(d[47]), "+f"(d[48]), "+f"(d[49]), "+f"(d[50]), "+f"(d[51]), "+f"(d[52]), "+f"(d[53]), "+f"(d[54]), "+f"(d[55]), "+f"(d[56]), "+f"(d[57]), "+f"(d[58]), "+f"(d[59]), "+f"(d[60]), "+f"(d[61]), "+f"(d[62]), "+f"(d[63]), "+f"(d[64]), "+f"(d[65]), "+f"(d[66]), "+f"(d[67]), "+f"(d[68]), "+f"(d[69]), "+f"(d[70]), "+f"(d[71]), "+f"(d[72]), "+f"(d[73]), "+f"(d[74]), "+f"(d[75]), "+f"(d[76]), "+f"(d[77]), "+f"(d[78]), "+f"(d[79]), "+f"(d[80]), "+f"(d[81]), "+f"(d[82]), "+f"(d[83]), "+f"(d[84]), "+f"(d[85]), "+f"(d[86]), "+f"(d[87]), "+f"(d[88]), "+f"(d[89]), "+f"(d[90]), "+f"(d[91]), "+f"(d[92]), "+f"(d[93]), "+f"(d[94]), "+f"(d[95]), "+f"(d[96]), "+f"(d[97]), "+f"(d[98]), "+f"(d[99]), "+f"(d[100]), "+f"(d[101]), "+f"(d[102]), "+f"(d[103]), "+f"(d[104]), "+f"(d[105]), "+f"(d[106]), "+f"(d[107]), "+f"(d[108]), "+f"(d[109]), "+f"(d[110]), "+f"(d[111]), "+f"(d[112]), "+f"(d[113]), "+f"(d[114]), "+f"(d[115]), "+f"(d[116]), "+f"(d[117]), "+f"(d[118]), "+f"(d[119]), "+f"(d[120]), "+f"(d[121]), "+f"(d[122]), "+f"(d[123]), "+f"(d[124]), "+f"(d[125]), "+f"(d[126]), "+f"(d[127])
    : "r"(a[0]), "r"(a[1]), "r"(a[2]), "r"(a[3]), "r"(descB), "r"(accum));
}
template <> __device__ __forceinline__ void wgmma_rs<232>(float* d, const uint32_t* a, uint32_t descB, uint32_t accum) {
  asm volatile(
    "{\n.reg .pred p;\n.reg .b64 db;\n"
    "setp.ne.b32 p, %121, 0;\n"
    "mov.b64 db, {%120, 0x40000040};\n"
    "wgmma.mma_async.sync.aligned.m64n232k16.f32.bf16.bf16 "
    "{%0, %1, %2, %3, %4, %5, %6, %7, %8, %9, %10, %11, %12, %13, %14, %15, %16, %17, %18, %19, %20, %21, %22, %23, %24, %25, %26, %27, %28, %29, %30, %31, %32, %33, %34, %35, %36, %37, %38, %39, %40, %41, %42, %43, %44, %45, %46, %47, %48, %49, %50, %51, %52, %53, %54, %55, %56, %57, %58, %59, %60, %61, %62, %63, %64, %65, %66, %67, %68, %69, %70, %71, %72, %73, %74, %75, %76, %77, %78, %79, %80, %81, %82, %83, %84, %85, %86, %87, %88, %89, %90, %91, %92, %93, %94, %95, %96, %97, %98, %99, %100, %101, %102, %103, %104, %105, %106, %107, %108, %109, %110, %111, %112, %113, %114, %115}, "
    "{%116, %117, %118, %119}, db, p, 1, 1, 0;\n"
    "}\n"
    : "+f"(d[0]), "+f"(d[1]), "+f"(d[2]), "+f"(d[3]), "+f"(d[4]), "+f"(d[5]), "+f"(d[6]), "+f"(d[7]), "+f"(d[8]), "+f"(d[9]), "+f"(d[10]), "+f"(d[11]), "+f"(d[12]), "+f"(d[13]), "+f"(d[14]), "+f"(d[15]), "+f"(d[16]), "+f"(d[17]), "+f"(d[18]), "+f"(d[19]), "+f"(d[20]), "+f"(d[21]), "+f"(d[22]), "+f"(d[23]), "+f"(d[24]), "+f"(d[25]), "+f"(d[26]), "+f"(d[27]), "+f"(d[28]), "+f"(d[29]), "+f"(d[30]), "+f"(d[31]), "+f"(d[32]), "+f"(d[33]), "+f"(d[34]), "+f"(d[35]), "+f"(d[36]), "+f"(d[37]), "+f"(d[38]), "+f"(d[39]), "+f"(d[40]), "+f"(d[41]), "+f"(d[42]), "+f"(d[43]), "+f"(d[44]), "+f"(d[45]), "+f"(d[46]), "+f"(d[47]), "+f"(d[48]), "+f"(d[49]), "+f"(d[50]), "+f"(d[51]), "+f"(d[52]), "+f"(d[53]), "+f"(d[54]), "+f"(d[55]), "+f"(d[56]), "+f"(d[57]), "+f"(d[58]), "+f"(d[59]), "+f"(d[60]), "+f"(d[61]), "+f"(d[62]), "+f"(d[63]), "+f"(d[64]), "+f"(d[65]), "+f"(d[66]), "+f"(d[67]), "+f"(d[68]), "+f"(d[69]), "+f"(d[70]), "+f"(d[71]), "+f"(d[72]), "+f"(d[73]), "+f"(d[74]), "+f"(d[75]), "+f"(d[76]), "+f"(d[77]), "+f"(d[78]), "+f"(d[79]), "+f"(d[80]), "+f"(d[81]), "+f"(d[82]), "+f"(d[83]), "+f"(d[84]), "+f"(d[85]), "+f"(d[86]), "+f"(d[87]), "+f"(d[88]), "+f"(d[89]), "+f"(d[90]), "+f"(d[91]), "+f"(d[92]), "+f"(d[93]), "+f"(d[94]), "+f"(d[95]), "+f"(d[96]), "+f"(d[97]), "+f"(d[98]), "+f"(d[99]), "+f"(d[100]), "+f"(d[101]), "+f"(d[102]), "+f"(d[103]), "+f"(d[104]), "+f"(d[105]), "+f"(d[106]), "+f"(d[107]), "+f"(d[108]), "+f"(d[109]), "+f"(d[110]), "+f"(d[111]), "+f"(d[112]), "+f"(d[113]), "+f"(d[114]), "+f"(d[115])
    : "r"(a[0]), "r"(a[1]), "r"(a[2]), "r"(a[3]), "r"(descB), "r"(accum));
}
template <> __device__ __forceinline__ void wgmma_rs<192>(float* d, const uint32_t* a, uint32_t descB, uint32_t accum) {
  asm volatile(
    "{\n.reg .pred p;\n.reg .b64 db;\n"
    "setp.ne.b32 p, %101, 0;\n"
    "mov.b64 db, {%100, 0x40000040};\n"
    "wgmma.mma_async.sync.aligned.m64n192k16.f32.bf16.bf16 "
    "{%0, %1, %2, %3, %4, %5, %6, %7, %8, %9, %10, %11, %12, %13, %14, %15, %16, %17, %18, %19, %20, %21, %22, %23, %24, %25, %26, %27, %28, %29, %30, %31, %32, %33, %34, %35, %36, %37, %38, %39, %40, %41, %42, %43, %44, %45, %46, %47, %48, %49, %50, %51, %52, %53, %54, %55, %56, %57, %58, %59, %60, %61, %62, %63, %64, %65, %66, %67, %68, %69, %70, %71, %72, %73, %74, %75, %76, %77, %78, %79, %80, %81, %82, %83, %84, %85, %86, %87, %88, %89, %90, %91, %92, %93, %94, %95}, "
    "{%96, %97, %98, %99}, db, p, 1, 1, 0;\n"
    "}\n"
    : "+f"(d[0]), "+f"(d[1]), "+f"(d[2]), "+f"(d[3]), "+f"(d[4]), "+f"(d[5]), "+f"(d[6]), "+f"(d[7]), "+f"(d[8]), "+f"(d[9]), "+f"(d[10]), "+f"(d[11]), "+f"(d[12]), "+f"(d[13]), "+f"(d[14]), "+f"(d[15]), "+f"(d[16]), "+f"(d[17]), "+f"(d[18]), "+f"(d[19]), "+f"(d[20]), "+f"(d[21]), "+f"(d[22]), "+f"(d[23]), "+f"(d[24]), "+f"(d[25]), "+f"(d[26]), "+f"(d[27]), "+f"(d[28]), "+f"(d[29]), "+f"(d[30]), "+f"(d[31]), "+f"(d[32]), "+f"(d[33]), "+f"(d[34]), "+f"(d[35]), "+f"(d[36]), "+f"(d[37]), "+f"(d[38]), "+f"(d[39]), "+f"(d[40]), "+f"(d[41]), "+f"(d[42]), "+f"(d[43]), "+f"(d[44]), "+f"(d[45]), "+f"(d[46]), "+f"(d[47]), "+f"(d[48]), "+f"(d[49]), "+f"(d[50]), "+f"(d[51]), "+f"(d[52]), "+f"(d[53]), "+f"(d[54]), "+f"(d[55]), "+f"(d[56]), "+f"(d[57]), "+f"(d[58]), "+f"(d[59]), "+f"(d[60]), "+f"(d[61]), "+f"(d[62]), "+f"(d[63]), "+f"(d[64]), "+f"(d[65]), "+f"(d[66]), "+f"(d[67]), "+f"(d[68]), "+f"(d[69]), "+f"(d[70]), "+f"(d[71]), "+f"(d[72]), "+f"(d[73]), "+f"(d[74]), "+f"(d[75]), "+f"(d[76]), "+f"(d[77]), "+f"(d[78]), "+f"(d[79]), "+f"(d[80]), "+f"(d[81]), "+f"(d[82]), "+f"(d[83]), "+f"(d[84]), "+f"(d[85]), "+f"(d[86]), "+f"(d[87]), "+f"(d[88]), "+f"(d[89]), "+f"(d[90]), "+f"(d[91]), "+f"(d[92]), "+f"(d[93]), "+f"(d[94]), "+f"(d[95])
    : "r"(a[0]), "r"(a[1]), "r"(a[2]), "r"(a[3]), "r"(descB), "r"(accum));
}
template <> __device__ __forceinline__ void wgmma_rs<88>(float* d, const uint32_t* a, uint32_t descB, uint32_t accum) {
  asm volatile(
    "{\n.reg .pred p;\n.reg .b64 db;\n"
    "setp.ne.b32 p, %49, 0;\n"
    "mov.b64 db, {%48, 0x40000040};\n"
    "wgmma.mma_async.sync.aligned.m64n88k16.f32.bf16.bf16 "
    "{%0, %1, %2, %3, %4, %5, %6, %7, %8, %9, %10, %11, %12, %13, %14, %15, %16, %17, %18, %19, %20, %21, %22, %23, %24, %25, %26, %27, %28, %29, %30, %31, %32, %33, %34, %35, %36, %37, %38, %39, %40, %41, %42, %43}, "
    "{%44, %45, %46, %47}, db, p, 1, 1, 0;\n"
    "}\n"
    : "+f"(d[0]), "+f"(d[1]), "+f"(d[2]), "+f"(d[3]), "+f"(d[4]), "+f"(d[5]), "+f"(d[6]), "+f"(d[7]), "+f"(d[8]), "+f"(d[9]), "+f"(d[10]), "+f"(d[11]), "+f"(d[12]), "+f"(d[13]), "+f"(d[14]), "+f"(d[15]), "+f"(d[16]), "+f"(d[17]), "+f"(d[18]), "+f"(d[19]), "+f"(d[20]), "+f"(d[21]), "+f"(d[22]), "+f"(d[23]), "+f"(d[24]), "+f"(d[25]), "+f"(d[26]), "+f"(d[27]), "+f"(d[28]), "+f"(d[29]), "+f"(d[30]), "+f"(d[31]), "+f"(d[32]), "+f"(d[33]), "+f"(d[34]), "+f"(d[35]), "+f"(d[36]), "+f"(d[37]), "+f"(d[38]), "+f"(d[39]), "+f"(d[40]), "+f"(d[41]), "+f"(d[42]), "+f"(d[43])
    : "r"(a[0]), "r"(a[1]), "r"(a[2]), "r"(a[3]), "r"(descB), "r"(accum));
}
template <> __device__ __forceinline__ void wgmma_rs<64>(float* d, const uint32_t* a, uint32_t descB, uint32_t accum) {
  asm volatile(
    "{\n.reg .pred p;\n.reg .b64 db;\n"
    "setp.ne.b32 p, %37, 0;\n"
    "mov.b64 db, {%36, 0x40000040};\n"
    "wgmma.mma_async.sync.aligned.m64n64k16.f32.bf16.bf16 "
    "{%0, %1, %2, %3, %4, %5, %6, %7, %8, %9, %10, %11, %12, %13, %14, %15, %16, %17, %18, %19, %20, %21, %22, %23, %24, %25, %26, %27, %28, %29, %30, %31}, "
    "{%32, %33, %34, %35}, db, p, 1, 1, 0;\n"
    "}\n"
    : "+f"(d[0]), "+f"(d[1]), "+f"(d[2]), "+f"(d[3]), "+f"(d[4]), "+f"(d[5]), "+f"(d[6]), "+f"(d[7]), "+f"(d[8]), "+f"(d[9]), "+f"(d[10]), "+f"(d[11]), "+f"(d[12]), "+f"(d[13]), "+f"(d[14]), "+f"(d[15]), "+f"(d[16]), "+f"(d[17]), "+f"(d[18]), "+f"(d[19]), "+f"(d[20]), "+f"(d[21]), "+f"(d[22]), "+f"(d[23]), "+f"(d[24]), "+f"(d[25]), "+f"(d[26]), "+f"(d[27]), "+f"(d[28]), "+f"(d[29]), "+f"(d[30]), "+f"(d[31])
    : "r"(a[0]), "r"(a[1]), "r"(a[2]), "r"(a[3]), "r"(descB), "r"(accum));
}
template <> __device__ __forceinline__ void wgmma_rs<40>(float* d, const uint32_t* a, uint32_t descB, uint32_t accum) {
  asm volatile(
    "{\n.reg .pred p;\n.reg .b64 db;\n"
    "setp.ne.b32 p, %25, 0;\n"
    "mov.b64 db, {%24, 0x40000040};\n"
    "wgmma.mma_async.sync.aligned.m64n40k16.f32.bf16.bf16 "
    "{%0, %1, %2, %3, %4, %5, %6, %7, %8, %9, %10, %11, %12, %13, %14, %15, %16, %17, %18, %19}, "
    "{%20, %21, %22, %23}, db, p, 1, 1, 0;\n"
    "}\n"
    : "+f"(d[0]), "+f"(d[1]), "+f"(d[2]), "+f"(d[3]), "+f"(d[4]), "+f"(d[5]), "+f"(d[6]), "+f"(d[7]), "+f"(d[8]), "+f"(d[9]), "+f"(d[10]), "+f"(d[11]), "+f"(d[12]), "+f"(d[13]), "+f"(d[14]), "+f"(d[15]), "+f"(d[16]), "+f"(d[17]), "+f"(d[18]), "+f"(d[19])
    : "r"(a[0]), "r"(a[1]), "r"(a[2]), "r"(a[3]), "r"(descB), "r"(accum));
}

template <int N> __device__ __forceinline__ void wgmma_rl(float* d, const uint32_t* a, uint64_t descB);
template <> __device__ __forceinline__ void wgmma_rl<96>(float* d, const uint32_t* a, uint64_t descB) {
  asm volatile(
    "wgmma.mma_async.sync.aligned.m64n96k16.f32.bf16.bf16 "
    "{%0, %1, %2, %3, %4, %5, %6, %7, %8, %9, %10, %11, %12, %13, %14, %15, %16, %17, %18, %19, %20, %21, %22, %23, %24, %25, %26, %27, %28, %29, %30, %31, %32, %33, %34, %35, %36, %37, %38, %39, %40, %41, %42, %43, %44, %45, %46, %47}, "
    "{%48, %49, %50, %51}, %52, 1, 1, 1, 0;\n"
    : "+f"(d[0]), "+f"(d[1]), "+f"(d[2]), "+f"(d[3]), "+f"(d[4]), "+f"(d[5]), "+f"(d[6]), "+f"(d[7]), "+f"(d[8]), "+f"(d[9]), "+f"(d[10]), "+f"(d[11]), "+f"(d[12]), "+f"(d[13]), "+f"(d[14]), "+f"(d[15]), "+f"(d[16]), "+f"(d[17]), "+f"(d[18]), "+f"(d[19]), "+f"(d[20]), "+f"(d[21]), "+f"(d[22]), "+f"(d[23]), "+f"(d[24]), "+f"(d[25]), "+f"(d[26]), "+f"(d[27]), "+f"(d[28]), "+f"(d[29]), "+f"(d[30]), "+f"(d[31]), "+f"(d[32]), "+f"(d[33]), "+f"(d[34]), "+f"(d[35]), "+f"(d[36]), "+f"(d[37]), "+f"(d[38]), "+f"(d[39]), "+f"(d[40]), "+f"(d[41]), "+f"(d[42]), "+f"(d[43]), "+f"(d[44]), "+f"(d[45]), "+f"(d[46]), "+f"(d[47])
    : "r"(a[0]), "r"(a[1]), "r"(a[2]), "r"(a[3]), "l"(descB));
}

template <int N> __device__ __forceinline__ void wgmma_ss(float* d, uint64_t descA, uint64_t descB, uint32_t accum);
template <> __device__ __forceinline__ void wgmma_ss<192>(float* d, uint64_t descA, uint64_t descB, uint32_t accum) {
  asm volatile(
    "{\n.reg .pred p;\n"
    "setp.ne.b32 p, %98, 0;\n"
    "wgmma.mma_async.sync.aligned.m64n192k16.f32.bf16.bf16 "
    "{%0, %1, %2, %3, %4, %5, %6, %7, %8, %9, %10, %11, %12, %13, %14, %15, %16, %17, %18, %19, %20, %21, %22, %23, %24, %25, %26, %27, %28, %29, %30, %31, %32, %33, %34, %35, %36, %37, %38, %39, %40, %41, %42, %43, %44, %45, %46, %47, %48, %49, %50, %51, %52, %53, %54, %55, %56, %57, %58, %59, %60, %61, %62, %63, %64, %65, %66, %67, %68, %69, %70, %71, %72, %73, %74, %75, %76, %77, %78, %79, %80, %81, %82, %83, %84, %85, %86, %87, %88, %89, %90, %91, %92, %93, %94, %95}, "
    "%96, %97, p, 1, 1, 0, 0;\n"
    "}\n"
    : "+f"(d[0]), "+f"(d[1]), "+f"(d[2]), "+f"(d[3]), "+f"(d[4]), "+f"(d[5]), "+f"(d[6]), "+f"(d[7]), "+f"(d[8]), "+f"(d[9]), "+f"(d[10]), "+f"(d[11]), "+f"(d[12]), "+f"(d[13]), "+f"(d[14]), "+f"(d[15]), "+f"(d[16]), "+f"(d[17]), "+f"(d[18]), "+f"(d[19]), "+f"(d[20]), "+f"(d[21]), "+f"(d[22]), "+f"(d[23]), "+f"(d[24]), "+f"(d[25]), "+f"(d[26]), "+f"(d[27]), "+f"(d[28]), "+f"(d[29]), "+f"(d[30]), "+f"(d[31]), "+f"(d[32]), "+f"(d[33]), "+f"(d[34]), "+f"(d[35]), "+f"(d[36]), "+f"(d[37]), "+f"(d[38]), "+f"(d[39]), "+f"(d[40]), "+f"(d[41]), "+f"(d[42]), "+f"(d[43]), "+f"(d[44]), "+f"(d[45]), "+f"(d[46]), "+f"(d[47]), "+f"(d[48]), "+f"(d[49]), "+f"(d[50]), "+f"(d[51]), "+f"(d[52]), "+f"(d[53]), "+f"(d[54]), "+f"(d[55]), "+f"(d[56]), "+f"(d[57]), "+f"(d[58]), "+f"(d[59]), "+f"(d[60]), "+f"(d[61]), "+f"(d[62]), "+f"(d[63]), "+f"(d[64]), "+f"(d[65]), "+f"(d[66]), "+f"(d[67]), "+f"(d[68]), "+f"(d[69]), "+f"(d[70]), "+f"(d[71]), "+f"(d[72]), "+f"(d[73]), "+f"(d[74]), "+f"(d[75]), "+f"(d[76]), "+f"(d[77]), "+f"(d[78]), "+f"(d[79]), "+f"(d[80]), "+f"(d[81]), "+f"(d[82]), "+f"(d[83]), "+f"(d[84]), "+f"(d[85]), "+f"(d[86]), "+f"(d[87]), "+f"(d[88]), "+f"(d[89]), "+f"(d[90]), "+f"(d[91]), "+f"(d[92]), "+f"(d[93]), "+f"(d[94]), "+f"(d[95])
    : "l"(descA), "l"(descB), "r"(accum));
}
template <> __device__ __forceinline__ void wgmma_ss<184>(float* d, uint64_t descA, uint64_t descB, uint32_t accum) {
  asm volatile(
    "{\n.reg .pred p;\n"
    "setp.ne.b32 p, %94, 0;\n"
    "wgmma.mma_async.sync.aligned.m64n184k16.f32.bf16.bf16 "
    "{%0, %1, %2, %3, %4, %5, %6, %7, %8, %9, %10, %11, %12, %13, %14, %15, %16, %17, %18, %19, %20, %21, %22, %23, %24, %25, %26, %27, %28, %29, %30, %31, %32, %33, %34, %35, %36, %37, %38, %39, %40, %41, %42, %43, %44, %45, %46, %47, %48, %49, %50, %51, %52, %53, %54, %55, %56, %57, %58, %59, %60, %61, %62, %63, %64, %65, %66, %67, %68, %69, %70, %71, %72, %73, %74, %75, %76, %77, %78, %79, %80, %81, %82, %83, %84, %85, %86, %87, %88, %89, %90, %91}, "
    "%92, %93, p, 1, 1, 0, 0;\n"
    "}\n"
    : "+f"(d[0]), "+f"(d[1]), "+f"(d[2]), "+f"(d[3]), "+f"(d[4]), "+f"(d[5]), "+f"(d[6]), "+f"(d[7]), "+f"(d[8]), "+f"(d[9]), "+f"(d[10]), "+f"(d[11]), "+f"(d[12]), "+f"(d[13]), "+f"(d[14]), "+f"(d[15]), "+f"(d[16]), "+f"(d[17]), "+f"(d[18]), "+f"(d[19]), "+f"(d[20]), "+f"(d[21]), "+f"(d[22]), "+f"(d[23]), "+f"(d[24]), "+f"(d[25]), "+f"(d[26]), "+f"(d[27]), "+f"(d[28]), "+f"(d[29]), "+f"(d[30]), "+f"(d[31]), "+f"(d[32]), "+f"(d[33]), "+f"(d[34]), "+f"(d[35]), "+f"(d[36]), "+f"(d[37]), "+f"(d[38]), "+f"(d[39]), "+f"(d[40]), "+f"(d[41]), "+f"(d[42]), "+f"(d[43]), "+f"(d[44]), "+f"(d[45]), "+f"(d[46]), "+f"(d[47]), "+f"(d[48]), "+f"(d[49]), "+f"(d[50]), "+f"(d[51]), "+f"(d[52]), "+f"(d[53]), "+f"(d[54]), "+f"(d[55]), "+f"(d[56]), "+f"(d[57]), "+f"(d[58]), "+f"(d[59]), "+f"(d[60]), "+f"(d[61]), "+f"(d[62]), "+f"(d[63]), "+f"(d[64]), "+f"(d[65]), "+f"(d[66]), "+f"(d[67]), "+f"(d[68]), "+f"(d[69]), "+f"(d[70]), "+f"(d[71]), "+f"(d[72]), "+f"(d[73]), "+f"(d[74]), "+f"(d[75]), "+f"(d[76]), "+f"(d[77]), "+f"(d[78]), "+f"(d[79]), "+f"(d[80]), "+f"(d[81]), "+f"(d[82]), "+f"(d[83]), "+f"(d[84]), "+f"(d[85]), "+f"(d[86]), "+f"(d[87]), "+f"(d[88]), "+f"(d[89]), "+f"(d[90]), "+f"(d[91])
    : "l"(descA), "l"(descB), "r"(accum));
}

template <int N> struct IC { static constexpr int v = N; };

__device__ __forceinline__ void stmatrix_x4_t(uint32_t addr, uint32_t r0, uint32_t r1, uint32_t r2, uint32_t r3) {
  asm volatile("stmatrix.sync.aligned.m8n8.x4.trans.shared.b16 [%0], {%1, %2, %3, %4};"
               ::"r"(addr), "r"(r0), "r"(r1), "r"(r2), "r"(r3) : "memory");
}
__device__ __forceinline__ void ldmatrix_x4(uint32_t* r, uint32_t addr) {
  asm volatile("ldmatrix.sync.aligned.m8n8.x4.shared.b16 {%0, %1, %2, %3}, [%4];"
               : "=r"(r[0]), "=r"(r[1]), "=r"(r[2]), "=r"(r[3]) : "r"(addr) : "memory");
}
__device__ __forceinline__ uint32_t pack_bf16(float a, float b) {
  __nv_bfloat162 v = __floats2bfloat162_rn(a, b);
  return *reinterpret_cast<uint32_t*>(&v);
}
__device__ __forceinline__ uint32_t prmt(uint32_t a, uint32_t b, uint32_t s) {
  uint32_t d;
  asm("prmt.b32 %0, %1, %2, %3;" : "=r"(d) : "r"(a), "r"(b), "r"(s));
  return d;
}
__device__ __forceinline__ uint32_t lds32(uint32_t a) {
  uint32_t v;
  asm volatile("ld.shared.u32 %0, [%1];" : "=r"(v) : "r"(a) : "memory");
  return v;
}
__device__ __forceinline__ void lds128(uint32_t* v, uint32_t a) {
  asm volatile("ld.shared.v4.u32 {%0, %1, %2, %3}, [%4];" : "=r"(v[0]), "=r"(v[1]), "=r"(v[2]), "=r"(v[3]) : "r"(a) : "memory");
}
__device__ __forceinline__ void sts128(uint32_t a, const uint32_t* v) {
  asm volatile("st.shared.v4.u32 [%0], {%1, %2, %3, %4};" ::"r"(a), "r"(v[0]), "r"(v[1]), "r"(v[2]), "r"(v[3]) : "memory");
}
__device__ __forceinline__ void sts32(uint32_t a, uint32_t v) {
  asm volatile("st.shared.u32 [%0], %1;" ::"r"(a), "r"(v) : "memory");
}
__device__ __forceinline__ void wait_until(uint32_t t0, uint32_t at) {
  asm volatile(
      "{\n.reg .pred p;\n.reg .s32 r;\n"
      "SPIN:\n"
      "mov.u32 r, %%clock;\n"
      "sub.s32 r, %0, r;\n"
      "setp.gt.s32 p, r, 0;\n"
      "shr.s32 r, r, %1;\n"
      "@p nanosleep.u32 r;\n"
      "@p bra.uni SPIN;\n}\n"
      ::"r"(t0 + at), "n"(NSH) : "memory");
}
__device__ __forceinline__ void spin_until(uint32_t t0, uint32_t at) {
  while ((uint32_t)clock() - t0 < at) {}
}
__device__ __forceinline__ void wait_count(const unsigned int* f, uint32_t& c) {
  asm volatile(
      "{\n.reg .pred p;\n.reg .u32 v;\n"
      "SPIN:\n"
      "ld.acquire.gpu.global.u32 v, [%1];\n"
      "add.u32 %0, %0, 16;\n"
      "setp.lt.u32 p, %0, 0x100000;\n"
      "setp.lt.and.u32 p, v, 64, p;\n"
      "@p nanosleep.u32 100;\n"
      "@p bra.uni SPIN;\n}\n"
      : "+r"(c) : "l"(f) : "memory");
}
template <int E>
__device__ __forceinline__ void ld_lut(uint32_t* v, const __nv_bfloat16* p) {
  asm volatile("ld.global.nc.u32 %0, [%1+%2];" : "=r"(v[E]) : "l"(p), "n"(((E & 3) * N_ + 8 * (E >> 2)) * 2));
  if constexpr (E < 7) ld_lut<E + 1>(v, p);
}
template <int OFF>
__device__ __forceinline__ void ld_codes4(uint32_t* w, const int* p) {
  asm volatile("ld.global.nc.L1::no_allocate.v4.u32 {%0, %1, %2, %3}, [%4+%5];" : "=r"(w[0]), "=r"(w[1]), "=r"(w[2]), "=r"(w[3]) : "l"(p), "n"(OFF));
}
__device__ __forceinline__ void ld_codes(uint32_t* w, const int* p) {
  ld_codes4<0>(w, p);
  ld_codes4<N_ * 4>(w + 4, p);
  ld_codes4<N_ * 32>(w + 8, p);
  ld_codes4<N_ * 36>(w + 12, p);
}
__device__ __forceinline__ void prefetch_map(const CUtensorMap* map) {
  asm volatile("prefetch.tensormap [%0];" ::"l"((uint64_t)map) : "memory");
}
template <int OFF>
__device__ __forceinline__ void ld_words(uint32_t* w, const uint8_t* p) {
  asm volatile("ld.relaxed.gpu.global.v4.u32 {%0, %1, %2, %3}, [%4+%5];" : "=r"(w[0]), "=r"(w[1]), "=r"(w[2]), "=r"(w[3]) : "l"(p), "n"(OFF) : "memory");
}
template <int OFF>
__device__ __forceinline__ void st_words(uint8_t* p, const uint32_t* w) {
  asm volatile("st.relaxed.gpu.global.v4.u32 [%0+%5], {%1, %2, %3, %4};" ::"l"(p), "r"(w[0]), "r"(w[1]), "r"(w[2]), "r"(w[3]), "n"(OFF) : "memory");
}

#define DBG(i)

__device__ __forceinline__ uint32_t word_key(uint32_t odd) { return 0xcdf00000u + (odd << 19); }
__device__ __forceinline__ uint32_t make_word(uint32_t c0, uint32_t c1, uint32_t c2, uint32_t c3, uint32_t key) {
  uint32_t p01, p23, n, w;
  asm("mad.lo.u32 %0, %1, 16, %2;" : "=r"(p01) : "r"(c1), "r"(c0));
  asm("mad.lo.u32 %0, %1, 16, %2;" : "=r"(p23) : "r"(c3), "r"(c2));
  asm("mad.lo.u32 %0, %1, 256, %2;" : "=r"(n) : "r"(p23), "r"(p01));
  asm("mad.lo.u32 %0, %1, 0x7fff, %2;" : "=r"(w) : "r"((n & 0x8888u) | key), "r"(n));
  return w;
}
struct Planes { uint32_t v[4][4]; };
__device__ __forceinline__ void lookup4(const Planes& pl, int c, uint32_t s, uint32_t sc, uint32_t& o0, uint32_t& o1) {
  uint32_t s2;
  asm("{\n.reg .b16 l, h;\n.reg .b32 t;\nmov.b32 {l, h}, %1;\nmov.b32 t, {h, h};\nmul.rn.f16x2 %0, t, %2;\n}\n" : "=r"(s2) : "r"(s), "r"(sc));
  const uint32_t lo = prmt(prmt(pl.v[0][2 * c], pl.v[1][2 * c], s), prmt(pl.v[2][2 * c], pl.v[3][2 * c], s), s2);
  const uint32_t hi = prmt(prmt(pl.v[0][2 * c + 1], pl.v[1][2 * c + 1], s), prmt(pl.v[2][2 * c + 1], pl.v[3][2 * c + 1], s), s2);
  o0 = prmt(lo, hi, 0x5140);
  o1 = prmt(lo, hi, 0x7362);
}
__device__ __forceinline__ void store_planes(uint32_t dst, const uint32_t* lv) {
#pragma unroll
  for (int h = 0; h < 2; h++) {
    uint32_t qp[4];
#pragma unroll
    for (int c = 0; c < 2; c++) {
      const uint32_t a = prmt(lv[4 * c], lv[4 * c + 1], h ? 0x7362 : 0x5140), b = prmt(lv[4 * c + 2], lv[4 * c + 3], h ? 0x7362 : 0x5140);
      qp[2 * c] = prmt(a, b, 0x5410);
      qp[2 * c + 1] = prmt(a, b, 0x7632);
    }
    sts128(dst + 64 * h, qp);
  }
}
__device__ __forceinline__ bool words_ok(const uint32_t* P, uint32_t tag) {
  return (P[0] & P[1] & P[2] & P[3] & P[4] & P[5] & P[6] & P[7] & tag) != 0;
}
template <int NJ>
__device__ __forceinline__ void stage_part(const float* a, uint32_t sts) {
#pragma unroll
  for (int j = 0; j < NJ; j++)
    stmatrix_x4_t(sts + 16 * j * 128, pack_bf16(a[8 * j], a[8 * j + 1]), pack_bf16(a[8 * j + 2], a[8 * j + 3]),
                  pack_bf16(a[8 * j + 4], a[8 * j + 5]), pack_bf16(a[8 * j + 6], a[8 * j + 7]));
}

template <int OFF>
__device__ __forceinline__ uint32_t lut_at(uint32_t tab, uint32_t c) {
  uint32_t v;
  asm volatile("ld.shared.u16 %0, [%1+%2];" : "=r"(v) : "r"(tab + 40 * c), "n"(OFF));
  return v;
}
template <int J>
__device__ __forceinline__ void convert_col(const uint32_t (*v)[4], uint32_t tab, uint8_t* dst) {
  uint32_t o[4];
#pragma unroll
  for (int i = 0; i < 4; i++) {
    const uint32_t a = lut_at<2 * J>(tab, v[2 * i][J]), b = lut_at<2 * J>(tab, v[2 * i + 1][J]);
    asm("mad.lo.u32 %0, %1, 65536, %2;" : "=r"(o[i]) : "r"(b), "r"(a));
  }
  st_words<2048 * J>(dst, o);
}

template <int J>
__device__ __forceinline__ void convert_shfl(const uint32_t (*v)[4], uint32_t e, uint8_t* dst) {
  uint32_t o[4];
#pragma unroll
  for (int i = 0; i < 4; i++) {
    uint32_t a, b;
    asm volatile("shfl.sync.idx.b32 %0, %1, %2, 0x101f, 0xffffffff;" : "=r"(a) : "r"(e), "r"(v[2 * i][J]));
    asm volatile("shfl.sync.idx.b32 %0, %1, %2, 0x101f, 0xffffffff;" : "=r"(b) : "r"(e), "r"(v[2 * i + 1][J]));
    o[i] = prmt(a, b, J & 1 ? 0x7632 : 0x5410);
  }
  st_words<2048 * J>(dst, o);
}

struct Maps { CUtensorMap m[NMAPS]; uint64_t desc; uint32_t tiles[66], jobs[396]; };
#define TILES() \
  const int fta = (te & 15) + rank, ftb = ((te >> 4) & 15) + rank, toka = (te >> 5) & 0x7f8, tokb = (te >> 13) & 0x7f8; \
  const bool big = fta < 12; \
  (void)toka; (void)big; (void)tokb
__global__ void __cluster_dims__(2, 1, 1) __launch_bounds__(NTHREADS, 1)
fused_kernel(unsigned int* __restrict__ count, const __nv_bfloat16* __restrict__ lut, uint8_t* __restrict__ gp,
             const int* __restrict__ qw, const uint8_t* __restrict__ xg, const __grid_constant__ Maps maps) {
  extern __shared__ __align__(1024) uint8_t smem_gen[];
  const uint32_t t0 = clock();
  const int tid = threadIdx.x;
  uint32_t cf[16];
  const int* src = qw + (((tid >> 8) * BK + 32 + (tid & 48) + ((tid >> 1) & 6)) * N_ + (blockIdx.x & 127) * 16 + (tid & 3) * 4);
  uint32_t ep0 = 0;
  if ((tid >> 6) == 2) {
    if (EPW) asm volatile("ld.relaxed.gpu.global.u32 %0, [%1];" : "=r"(ep0) : "l"(count) : "memory");
    ld_codes(cf, src);
  }
  const uint32_t te = maps.tiles[blockIdx.x >> 1];
  const int rank = blockIdx.x & 1;
  const uint32_t sl = smem_u32(smem_gen);
  auto bar = [&](int i) { return sl + OFF_BAR + 8 * i; };
  const int w12 = __shfl_sync(0xffffffffu, tid >> 5, 0);
  const int wg = w12 >> 2;
  const int warp = w12 & 3;
  const int lane = tid & 31;
  uint32_t bud = 0;
  if (__builtin_expect(wg == 0, 1)) {
    asm volatile("setmaxnreg.dec.sync.aligned.u32 72;");
    if (warp == 0) {
      if (lane == 0) {
#pragma unroll
        for (int i = 0; i < NBARS; i++) mbar_init(bar(i), i >= 4 && i < 8 ? 4 : 1);
        mbar_init(bar(B_LAST), 4);
        asm volatile("fence.mbarrier_init.release.cluster;" ::: "memory");
      }
      __syncwarp();
      cluster_arrive_relaxed();
      asm volatile("bar.arrive 4, 128;" ::: "memory");
      DBG(1);
      TILES();
      expect_w(bar(B_DIR), 2 * UNIT_BYTES);
      tma3_w(sl + 3 * STAGE_BYTES, &maps.m[M_D], bar(B_DIR), 0, 0, fta * 4);
      const int ca = TR1 && !big ? (TA - TC) * 128 : 0, cb = TR2 && big ? (TB - TD) * 128 : 0;
      const CUtensorMap *ma = &maps.m[M_XA + (ca ? rank : 0)], *mb = &maps.m[M_XB + (cb ? rank : 0)];
      expect_w(bar(B_FULL), X_BYTES - ca);
      cluster_wait();
      tma_mc_w(sl + rank * (X_BYTES / 2), ma, bar(B_FULL), 0, toka + rank * (TA / 2));
      DBG(2);
      expect_w(bar(B_LAST), SLAB_BYTES);
      wait_until(t0, XT0);
#pragma unroll 1
      for (int n = 1; n < 2 * KBLKS - 3; n++) {
        const int stage = n & 3;
        const bool first = n < KBLKS;
        const int rows = rank * (first ? TA / 2 : TB / 2);
        mbar_wait(bar(B_EMPTY + stage), ((n - 3) >> 2) & 1, bud);
        expect_w(bar(B_FULL + stage), STAGE_BYTES - (first ? ca : cb));
        tma_mc_w(sl + stage * STAGE_BYTES + rows * 128, first ? ma : mb, bar(B_FULL + stage),
                 (n & (KBLKS - 1)) * BK, (first ? toka : tokb) + rows);
        if (XPD && n >= XPS && n < KBLKS - XPD) {
          const uint8_t* a = xg + (((blockIdx.x & 127) * 16 + (lane >> 1)) * (K_ * 2) + (lane & 1) * 64 + (n + XPD) * 128);
          asm volatile("prefetch.global.L2 [%0];" ::"l"(a));
          if (!XPW) asm volatile("prefetch.global.L2 [%0+32];" ::"l"(a));
        }
        if (n <= KBLKS) {
          wait_until(t0, 32 * prmt((uint32_t)GATES, (uint32_t)(GATES >> 32), min(n, 7)));
          bulk_w(sl + ((n - 1) & 3) * STAGE_BYTES + X_BYTES, gp + (fta * KBLKS + n - 1) * SLAB_BYTES, SLAB_BYTES, bar(B_FULL + (n & 19)));
        }
        if (n == PN) wait_count(count + 32 * (1 + ((lds32(sl + OFF_EPOCH) & 256) ? 48 : 0) + 4 * ftb), bud);
        if (first) continue;
        if (n == KBLKS + 4 || n == KBLKS + 8) asm volatile("bar.sync %0, 64;" ::"r"(n & 8) : "memory");
        tma_w(sl + stage * STAGE_BYTES + TB * 128, &maps.m[M_W], bar(B_FULL + stage), (n - KBLKS) * BK, ftb * BF);
        tma_w(sl + stage * STAGE_BYTES + TB * 128 + 8192, &maps.m[M_W], bar(B_FULL + stage), (n - KBLKS) * BK, ftb * BF + 64);
      }
      const uint32_t s1 = sl + STAGE_BYTES, s2 = s1 + STAGE_BYTES, s3 = s2 + STAGE_BYTES;
      const CUtensorMap *mx = &maps.m[M_XB], *mw = &maps.m[M_W];
      DBG(220);
      mbar_wait(bar(B_EMPTY + 1), 0, bud);
      DBG(221);
      expect_w(bar(B_FULL + 1), STAGE_BYTES);
      tma_mc_w(s1 + rank * 12288, mx, bar(B_FULL + 1), (13 + rank) * BK, tokb);
      tma_w(s1 + 24576, mw, bar(B_FULL + 1), 13 * BK, ftb * BF);
      tma_w(s1 + 32768, mw, bar(B_FULL + 1), 14 * BK, ftb * BF);
      DBG(222);
      mbar_wait(bar(B_EMPTY + 2), 0, bud);
      DBG(223);
      asm volatile("bar.sync 15, 96;" ::: "memory");
      DBG(224);
      expect_w(bar(B_FULL + 2), 20480);
      if (!rank) tma_mc_w(s2, mx, bar(B_FULL + 2), 15 * BK, tokb);
      tma_w(s2 + 12288, mw, bar(B_FULL + 2), 15 * BK, ftb * BF);
      DBG(225);
      expect_w(bar(B_RDY), 24576);
      tma_w(s2 + 20480, mw, bar(B_RDY), 13 * BK, ftb * BF + 64);
      tma_w(s2 + 28672, mw, bar(B_RDY), 14 * BK, ftb * BF + 64);
      tma_w(sl + OFF_STG + 24576, mw, bar(B_RDY), 15 * BK, ftb * BF + 64);
      DBG(226);
      mbar_wait(bar(B_EMPTY + 3), 1, bud);
      DBG(227);
      expect_w(bar(B_FULL + 3), 36864 - 3 * cb);
      if (cb) mx++;
      tma_mc_w(s3 + rank * 12288, mx, bar(B_FULL + 3), (13 + rank) * BK, tokb + TB / 2);
      if (rank) tma_mc_w(s3 + 24576, mx, bar(B_FULL + 3), 15 * BK, tokb + TB / 2);
      asm volatile(ELECT "@p red.relaxed.gpu.global.add.u32 [%0], %1;\n}\n" ::"l"(count), "r"(blockIdx.x < 2 * NUM_CTAS - 256 ? 1 : 2) : "memory");
    } else {
      const int p = warp - 1;
      uint32_t ep;
      asm volatile("ld.relaxed.gpu.global.u32 %0, [%1];" : "=r"(ep) : "l"(count) : "memory");
      cluster_arrive_relaxed();
      prefetch_map(&maps.m[p + (TR1 && p == 2 && (te & 15) >= 12 ? rank : 0)]);
      asm volatile("prefetch.global.L2 [%0];" ::"l"(xg + (((blockIdx.x * 16 + p * 8 + (lane >> 2)) & (M_ - 1)) * (K_ * 2) + (lane & 3) * 32)));
      const uint32_t so = OFF_STG + p * UNIT_BYTES;
      const uint32_t ua = sl + so + (lane & 3) * 256 + (((lane >> 2) ^ (2 * (lane & 3))) << 4);
      asm volatile("bar.sync 4, 128;" ::: "memory");
      if (!EPW && p == 2) {
        sts32(sl + OFF_EPOCH, ep);
        asm volatile("bar.arrive 1, 288;" ::: "memory");
      }
      int r = blockIdx.x, u = 128 + U0(r, p);
      const uint32_t job = maps.jobs[3 * r + p];
      uint32_t ph = 0, odd;
#pragma unroll 1
      do {
        wait_until(t0, D0 + (u - 128) * PU / 4);
        expect_w(bar(B_SLOT + p), UNIT_BYTES);
        tma_w(sl + so, &maps.m[M_Q], bar(B_SLOT + p), (u & 63) * 32, (u & ~63) + 32);
        DBG(16 + 8 * p + 2 * (r / NUM_CTAS));
        uint8_t* dst = gp + (((((u & 63) >> 2) * KBLKS + (u >> 6)) * 4 + (u & 3)) * 2048 + (lane >> 2) * 256 + (lane & 3) * 16);
        mbar_wait(bar(B_SLOT + p), ph, bud);
        asm volatile("and.b32 %0, %1, 256;" : "=r"(odd) : "r"(ep));
        DBG(184 + 4 * p + r / NUM_CTAS);
        uint32_t w[4][4];
#pragma unroll
        for (int b = 0; b < 4; b++) {
          uint32_t v[4][4];
          lds128(v[0], ua + b * 2048);
          lds128(v[1], (ua ^ 16) + b * 2048 + 128);
          lds128(v[2], ua + b * 2048 + 1024);
          lds128(v[3], (ua ^ 16) + b * 2048 + 1024 + 128);
#pragma unroll
          for (int j = 0; j < 4; j++) w[j][b] = make_word(v[0][j], v[1][j], v[2][j], v[3][j], word_key(odd));
        }
        st_words<0>(dst, w[0]); st_words<64>(dst, w[1]); st_words<128>(dst, w[2]); st_words<192>(dst, w[3]);
        __syncwarp();
        DBG(17 + 8 * p + 2 * (r / NUM_CTAS));
        ph ^= 1;
        r += NUM_CTAS;
        u = ph ? u + 3 * NUM_CTAS : job & 2047;
      } while (u < 1024);
      const int l = (job >> 11) & 511;
      const int ls = (l * 1366) >> 16, cg = l - 48 * ls;
      unsigned int* cnt = count + (32 + 6 * __shfl_sync(0xffffffffu, odd, 0));
      prefetch_map(&maps.m[M_XB + p]);
      prefetch_map(&maps.m[M_Q2]);
      if (l < 384) {
        uint32_t e[8];
        const __nv_bfloat16* s = lut + ((lane & 15) * N_ + 2048 + cg * 32 + (lane & 16));
        asm volatile("ld.global.nc.v4.u32 {%0, %1, %2, %3}, [%4];" : "=r"(e[0]), "=r"(e[1]), "=r"(e[2]), "=r"(e[3]) : "l"(s));
        asm volatile("ld.global.nc.v4.u32 {%0, %1, %2, %3}, [%4+16];" : "=r"(e[4]), "=r"(e[5]), "=r"(e[6]), "=r"(e[7]) : "l"(s));
        wait_until(t0, (job >> 20) * 8);
        expect_w(bar(B_SLOT + p), 2 * UNIT_BYTES);
        tma3_w(sl + so, &maps.m[M_Q2], bar(B_SLOT + p), 2048 + cg * 32, ls * 16, 0);
        tma3_w(sl + so + 32768, &maps.m[M_Q2], bar(B_SLOT + p), 2048 + cg * 32, ls * 16, 4);
        DBG(22 + 8 * p);
        uint32_t tab = sl + OFF_TAB + p * 1536 + (SHF ? lane * 32 : (lane >> 4) * 644);
        if (SHF) {
          sts128(tab, e);
          sts128(tab + 16, e + 4);
        } else {
#pragma unroll
          for (int i = 0; i < 8; i++) sts32(tab + (lane & 15) * 40 + 4 * i, e[i]);
          __syncwarp();
        }
        uint8_t* dst = gp + (W_OFF + cg * 65536 + ls * 256 + (lane >> 4) * 32768 + (lane & 15) * 16);
        const uint32_t src = sl + so + (lane & 15) * 128 + ((((lane >> 2) & 4) ^ (lane & 7)) << 4);
        mbar_wait(bar(B_SLOT + p), ph, bud);
#pragma unroll 1
        for (int c = 0; c < 64; c += 16, tab += 8, dst += 8192) {
          uint32_t v[8][4];
#pragma unroll
          for (int i = 0; i < 8; i++) lds128(v[i], (src ^ c) + (i & 3) * 2048 + (i >> 2) * 32768);
          if (SHF) {
            asm volatile("ld.shared.v2.u32 {%0, %1}, [%2];" : "=r"(e[0]), "=r"(e[1]) : "r"(tab) : "memory");
            convert_shfl<0>(v, e[0], dst);
            convert_shfl<1>(v, e[0], dst);
            convert_shfl<2>(v, e[1], dst);
            convert_shfl<3>(v, e[1], dst);
          } else {
          convert_col<0>(v, tab, dst);
          convert_col<1>(v, tab, dst);
          convert_col<2>(v, tab, dst);
          convert_col<3>(v, tab, dst);
          }
        }
        __syncwarp();
        DBG(23 + 8 * p);
      }
      arrive_w(bar(B_LAST));
      if (l < 384)
        asm volatile(ELECT "@p fence.proxy.async.global;\n@p red.release.gpu.global.add.u32 [%0], %1;\n}\n"
                     ::"l"(cnt + 32 * ((cg & ~3) + min(ls >> 1, 2))), "r"(ls < 4 ? 8 : 4) : "memory");
      cluster_wait();
      TILES();
      prefetch_map(&maps.m[p ? M_O32 : M_W]);
      if (p > 0) {
        asm volatile("bar.sync %0, 160;" ::"r"(12 + p) : "memory");
        if (FEN) asm volatile("fence.proxy.async.shared::cta;" ::: "memory");
        uint32_t t1 = clock();
#pragma unroll 1
        for (int i = 0; i < TA; i += OB, t1 += PC * OB / 32) {
          wait_until(t1, 0);
          const int rr = min(i, (big ? TA : TC) - OB);
          store_w(&maps.m[M_O32], sl + OFF_STG + (p - 1) * 32768 + rr * 128, fta * BF + 64 * (p - 1), toka + rr);
        }
        bulk_wait_read();
        DBG(227 + p);
        asm volatile("bar.arrive 15, 96;" ::: "memory");
      } else {
        if (blockIdx.x < 48) count[32 * (50 + blockIdx.x) - (cnt - count)] = 0;
#pragma unroll 1
        for (int i = 1; i < 3; i++) {
          wait_count(cnt + 32 * (4 * ftb + i), bud);
          asm volatile("bar.arrive %0, 64;" ::"r"(8 * i - 8) : "memory");
        }
      }
    }
    asm volatile("exit;");
  }
  const int cw = wg - 1;
  TILES();
  cluster_arrive_relaxed();
  if (warp >= 2) {
    ld_lut<0>(cf, lut + (fta * BF + 4 * (lane & 3) * N_ + 64 * cw + 32 * (warp & 1) + (lane & 16) + ((lane >> 1) & 6)));
  } else if (cw) {
    spin_until(t0, S1D);
    ld_codes(cf, src);
  } else if (EPW) {
    sts32(sl + OFF_EPOCH, ep0);
    asm volatile("bar.arrive 1, 256;" ::: "memory");
  }
  if (EPW) {
    if (w12 >= 6) asm volatile("bar.sync 1, 256;" ::: "memory");
  } else asm volatile("bar.sync 1, 288;" ::: "memory");
  const uint32_t odd = lds32(sl + OFF_EPOCH) & 256;
  DBG(40 + w12);
  if (warp >= 2) store_planes(sl + OFF_PL + cw * 32768 + (warp & 1) * 1024 + (lane & 28) * 32 + (lane & 3) * 16, cf);
  else {
    uint8_t* dst = gp + (((blockIdx.x & 120) * 2 + cw) * SLAB_BYTES + (blockIdx.x & 7) * 1024 + (tid & 63) * 16);
    const uint32_t tb = sl + OFF_STG + 61440 + cw * 1024;
#pragma unroll
    for (int j = 0; j < 4; j++)
      sts32(tb + (lane & 3) * 256 + j * 64 + (lane & 12) * 4 + ((tid >> 2) & 12), make_word(cf[j], cf[4 + j], cf[8 + j], cf[12 + j], word_key(odd)));
    asm volatile("bar.sync %0, 64;" ::"r"(6 + cw) : "memory");
    lds128(cf, tb + (tid & 63) * 16);
    st_words<0>(dst, cf);
  }
  DBG(52 + w12);
  asm volatile("setmaxnreg.inc.sync.aligned.u32 216;");
  uint32_t rel = (tid & 127) < 2 ? mapa(bar(B_EMPTY), lane) : 0u;
  uint32_t tg = (w12 - 4) * 1024 + lane * 16;
  uint32_t tw = sl + X_BYTES + tg;
  const uint8_t* gt = gp + (tg + fta * KBLKS * SLAB_BYTES);
  uint32_t tag = (1u << 28) - (odd << 19), sc = 0x3c00 + 8 * odd;
  asm volatile("" : "+r"(tw), "+l"(gt), "+r"(rel), "+r"(tag), "+r"(sc));
  Planes pl;
  uint32_t A[16], P[8];
  float acc[TA / 2];
  DBG(64 + cw);
  if (PLF) {
  asm volatile("bar.sync %0, 128;" ::"r"(2 + cw) : "memory");
#pragma unroll
  for (int k = 0; k < 4; k++) lds128(pl.v[k], sl + OFF_PL + cw * 32768 + (tid & 124) * 16 + 16 * k);
  }
  {
    const uint32_t td = sl + 3 * STAGE_BYTES - 8192 + (w12 >> 1) * 4096 + (lane & 3) * 256 + ((((tid >> 3) & 4) ^ (lane >> 4) ^ (2 * (lane & 3))) << 4) + (lane & 12);
    mbar_wait(bar(B_DIR), 0, bud);
    DBG(88 + cw);
#pragma unroll
    for (int k = 0; k < 4; k++) {
      const uint32_t a = (td ^ ((k & 2) << 4)) + (k & 1) * 2048;
      P[2 + (k & 1) + 2 * (k & 2)] = make_word(lds32(a), lds32((a ^ 16) + 128), lds32(a + 1024), lds32((a ^ 16) + 1152), word_key(odd));
    }
  }
  if (!PLF) {
  asm volatile("bar.sync %0, 128;" ::"r"(2 + cw) : "memory");
#pragma unroll
  for (int k = 0; k < 4; k++) lds128(pl.v[k], sl + OFF_PL + cw * 32768 + (tid & 124) * 16 + 16 * k);
  }
  mbar_wait(bar(B_FULL), 0, bud);
  DBG(66 + cw);
  auto tile1 = [&](auto nh) {
    uint32_t d = UD, dn, fb = bar(B_FULL + 1), pa = 0;
#pragma unroll 1
    for (int n = 0; n < KBLKS; n++) {
      bool ok;
#pragma unroll
      for (int b = 0; b < 4; b++) {
        const int m = n + 1;
        if (b == WB && !EP1) mbar_wait_fast(fb, (m >> 2) & 1, bud);
        if (b == WB && EP1 == 1 && !ok) mbar_wait(fb, (m >> 2) & 1, bud);
        if (b == 1 && EP1 == 3) ok = mbar_test(fb, (m >> 2) & 1);
        if (b == 1 && EP1 == 5) ok = mbar_peek(fb, (m >> 2) & 1);
        if (b == 2 && EP1 >= 4 && __builtin_expect(!ok, 0)) {
          mbar_wait(fb, (m >> 2) & 1, bud);
          lds128(P, tw + pa);
          lds128(P + 4, tw + pa + 512);
        }
        if (b == 2) {
#pragma unroll 1
          while (__builtin_expect(!words_ok(P, tag), 0)) {
            if ((bud += 16) >= 0x100000) break;
            asm volatile("{\n.reg .u64 a;\nmad.wide.u32 a, %8, 8192, %9;\nld.relaxed.gpu.global.v4.u32 {%0, %1, %2, %3}, [a];\n"
                         "ld.relaxed.gpu.global.v4.u32 {%4, %5, %6, %7}, [a+512];\n}\n"
                         : "=r"(P[0]), "=r"(P[1]), "=r"(P[2]), "=r"(P[3]), "=r"(P[4]), "=r"(P[5]), "=r"(P[6]), "=r"(P[7]) : "r"(n), "l"(gt) : "memory");
          }
          __syncwarp();
        }
        lookup4(pl, 0, P[b ^ 2], sc, A[4 * b], A[4 * b + 2]);
        lookup4(pl, 1, P[4 + (b ^ 2)], sc, A[4 * b + 1], A[4 * b + 3]);
        if (b == 1) {
          if ((EP1 == 2 || EP1 == 3) && !ok) mbar_wait(fb, (m >> 2) & 1, bud);
          lds128(P, tw + pa);
          lds128(P + 4, tw + pa + 512);
        }
        if (b == 3) {
          asm volatile("mad.lo.u32 %0, %1, %3, %2;" : "=r"(dn) : "r"(m & 3), "r"(UD), "n"(STAGE_BYTES / 16));
          asm volatile("mad.lo.u32 %0, %1, 8, %2;" : "=r"(fb) : "r"((m + 1) & 19), "r"(bar(B_FULL)));
          asm volatile("mul.lo.u32 %0, %1, %2;" : "=r"(pa) : "r"(m & 3), "n"(STAGE_BYTES));
        }
        if (((WD >> (4 * b)) & 3) == 1) wgmma_wait<1>();
        if (((WD >> (4 * b)) & 3) == 2) wgmma_wait<2>();
        if (b == RB) mbar_arrive_remote_if(rel + 8 * ((n - 1) & 3), rel);
        if (b == S1B && n == S1N && cw == 1) asm volatile("bar.sync 9, 256;" ::: "memory");
        if (b == 0 && (EP1 == 1 || EP1 == 2)) ok = mbar_test(fb, (m >> 2) & 1);
        if (b == 0 && EP1 == 4) ok = mbar_peek(fb, (m >> 2) & 1);
        wgmma_fence();
        if constexpr (ONE) wgmma_rs<decltype(nh)::v + TB>(acc, A + 4 * b, d + 2 * b, b > 0 || n != 0);
        else {
          wgmma_rs<decltype(nh)::v>(acc + TB / 2, A + 4 * b, d + 2 * b + TB * 8, b > 0 || n != 0);
          wgmma_rs<TB>(acc, A + 4 * b, d + 2 * b, b > 0 || n != 0);
        }
        wgmma_commit();
      }
      d = dn;
    }
  };
  if (big) tile1(IC<TA - TB>()); else tile1(IC<TC - TB>());
  if (cw != 1) asm volatile("bar.arrive 9, 256;" ::: "memory");
  const uint32_t stg = sl + OFF_STG + cw * 32768;
  const uint32_t so8 = stg + ((lane & 7) + ((lane >> 4) << 3)) * 128 + (((2 * warp + ((lane >> 3) & 1)) ^ (lane & 7)) << 4);
  DBG(212 + cw);
  mbar_wait(bar(B_FULL), 0, bud);
  DBG(214 + cw);
  if (NP > 1 && !W17) mbar_wait(bar(B_FULL + 1), 0, bud);
  DBG(216 + cw);
  const uint64_t ub = maps.desc, ua = ub + (TB * 8 + cw * 512);
  wgmma_wait<0>();
  mbar_arrive_remote_if(rel + 24, rel);
  fence_regs(acc);
  DBG(68 + cw);
  {
    uint32_t o[64];
#pragma unroll
    for (int k = 0; k < 48; k++) o[k] = pack_bf16(acc[2 * k], acc[2 * k + 1]);
#pragma unroll
    for (int k = 0; k < 48; k++) asm volatile("" : "+r"(o[k]) :: "memory");
    DBG(92 + cw);
    wgmma_fence();
#pragma unroll
    for (int b = 0; b < 4 * NP; b++) {
      const int so = (b >> 2) * (STAGE_BYTES / 16) + 2 * (b & 3);
      if (b == 4 && W17) mbar_wait(bar(B_FULL + 1), 0, bud);
      wgmma_ss<TB>(acc, ua + so, ub + so, b != 0);
      if ((b & 3) == 3 || b == 4) wgmma_commit();
      if (b == 0) {
#pragma unroll
        for (int k = 48; k < 64; k++) o[k] = pack_bf16(acc[2 * k], acc[2 * k + 1]);
      }
      if (b == 4) {
        wgmma_wait<1>();
        mbar_arrive_remote_if(rel, rel);
      }
#pragma unroll
      for (int j = 0; j < 16; j++)
        if (j * NSB / 16 + SB0 == b) stmatrix_x4_t(so8 + j * 2048, o[4 * j], o[4 * j + 1], o[4 * j + 2], o[4 * j + 3]);
    }
  }
  if (!FEN) asm volatile("fence.proxy.async.shared::cta;" ::: "memory");
  asm volatile("bar.arrive %0, 160;" ::"r"(13 + cw) : "memory");
  cluster_wait();
  DBG(70 + cw);
  auto tile2 = [&](auto nt) {
#pragma unroll 1
    for (int n = NP; n < KBLKS - 3; n++) {
      const uint32_t so = (n & 3) * (STAGE_BYTES / 16);
      mbar_wait_fast(bar(B_FULL) + 8 * (n & 3), (n >> 2) & 1, bud);
      wgmma_fence();
      wgmma_ss<decltype(nt)::v>(acc, ua + so, ub + so, 1);
      wgmma_commit();
      wgmma_wait<1>();
      mbar_arrive_remote_if(rel + 8 * ((n - 1) & 3), rel);
#pragma unroll
      for (int b = 1; b < 4; b++) wgmma_ss<decltype(nt)::v>(acc, ua + so + 2 * b, ub + so + 2 * b, 1);
      wgmma_commit();
    }
  };
  if (big) tile2(IC<TD>()); else tile2(IC<TB>());
  uint32_t W[48];
  float c2[TB / 2];
  DBG(72 + cw);
  const uint32_t wa = sl + (warp * 16 + (lane & 15)) * 128 + (((lane >> 4) ^ (lane & 7)) << 4);
  const uint32_t w0 = wa + (cw ? 2 * STAGE_BYTES + 20480 : STAGE_BYTES + 24576), w2 = wa + (cw ? OFF_STG + 24576 : 2 * STAGE_BYTES + 12288);
  mbar_wait(bar(B_FULL + 1), 1, bud);
  mbar_wait(bar(cw ? B_RDY : UPF == 2 ? B_FULL + 2 : B_FULL + 1), 1, bud);
#pragma unroll
  for (int b = 0; b < 8; b++) ldmatrix_x4(W + 4 * b, (w0 ^ ((b & 3) << 5)) + (b >> 2) * 8192);
  if (UPF) {
    if (UPF == 1) mbar_wait(bar(B_FULL + 2), 1, bud);
    DBG(218 + cw);
#pragma unroll
    for (int b = 0; b < 4; b++) ldmatrix_x4(W + 32 + 4 * b, w2 ^ (b << 5));
  }
  const uint64_t dl = ub + STAGE_BYTES / 16;
  wgmma_wait<0>();
#pragma unroll
  for (int k = 0; k < TB / 2; k++) asm volatile("mov.b32 %0, %1;" : "=f"(c2[k]) : "f"(acc[k]) : "memory");
#pragma unroll
  for (int h = 0; h < 2; h++) {
    if (h) mbar_wait(bar(B_FULL + 3), 1, bud);
    if (h || cw) asm volatile("bar.sync %0, 256;" ::"r"(9 + 2 * h + cw) : "memory");
    DBG(74 + 6 * h + cw);
    auto half = [&](auto nn) {
      bool ok = false;
      wgmma_fence();
#pragma unroll
      for (int i = 0; i < 12; i++) {
        if (!UPF && h == 0 && EP2 >= 0 && i == EP2) ok = mbar_test(bar(B_FULL + 2), 1);
        if (!UPF && h == 0 && i == MI) {
          if (!ok) mbar_wait(bar(B_FULL + 2), 1, bud);
#pragma unroll
          for (int b = 0; b < 4; b++) ldmatrix_x4(W + 32 + 4 * b, w2 ^ (b << 5));
        }
        if (!UPF && h == 0 && i == 8) wgmma_fence();
        const int off = (h ? 2 * STAGE_BYTES + (i >> 2) * 12288 : i < 8 ? (i >> 2) * 12288 : STAGE_BYTES) / 16 + 2 * (i & 3);
        if constexpr (decltype(nn)::v == 96) wgmma_rl<96>(c2 + 48 * h, W + 4 * i, dl + off);
        else wgmma_rs<decltype(nn)::v>(c2 + 48 * h, W + 4 * i, UD + STAGE_BYTES / 16 + off, 1);
        if (i == NSI - 1) wgmma_commit();
      }
      wgmma_commit();
    };
    if (N88 && h && big) half(IC<TD - TB / 2>()); else half(IC<TB / 2>());
    wgmma_wait<1>();
    if (!h || !cw) asm volatile("bar.arrive %0, 256;" ::"r"(10 + 2 * h + cw) : "memory");
    const int r2 = h ? (big ? TD - 96 : TB - 96) : 0;
    wgmma_wait<0>();
#pragma unroll
    for (int k = 0; k < 48; k++) asm volatile("" : "+f"(c2[48 * h + k]) :: "memory");
    DBG(76 + 6 * h + cw);
    stage_part<6>(c2 + 48 * h, so8 + 96 * 128 * h);
    asm volatile("fence.proxy.async.shared::cta;" ::: "memory");
    asm volatile("bar.sync %0, 128;" ::"r"(2 + cw) : "memory");
    if (O24) store_w(&maps.m[M_O96], stg + (r2 + 24 * warp) * 128, 2048 + ftb * BF + 64 * cw, tokb + r2 + 24 * warp);
    else if (warp == 0) store_w(&maps.m[M_O96], stg + r2 * 128, 2048 + ftb * BF + 64 * cw, tokb + r2);
    DBG(78 + 6 * h + cw);
  }
  bulk_wait_read();
}

typedef CUresult (*EncodeFn)(CUtensorMap*, CUtensorMapDataType, cuuint32_t, void*, const cuuint64_t*, const cuuint64_t*,
                             const cuuint32_t*, const cuuint32_t*, CUtensorMapInterleave, CUtensorMapSwizzle,
                             CUtensorMapL2promotion, CUtensorMapFloatOOBfill);

}

extern "C" void kernel_launch(void* const* d_in, const int* in_sizes, int n_in, void* d_out, int out_size) {
  const __nv_bfloat16* x = (const __nv_bfloat16*)d_in[0];
  const int* qw = (const int*)d_in[1];
  const __nv_bfloat16* lut = (const __nv_bfloat16*)d_in[2];

  static EncodeFn enc = nullptr;
  static unsigned int* count = nullptr;
  static uint8_t* gp = nullptr;
  if (!enc) {
    cudaDriverEntryPointQueryResult q;
    void* fn = nullptr;
    cudaGetDriverEntryPoint("cuTensorMapEncodeTiled", &fn, cudaEnableDefault, &q);
    enc = (EncodeFn)fn;
    cudaGetSymbolAddress((void**)&count, g_count);
    cudaGetSymbolAddress((void**)&gp, g_p);
    cudaFuncSetAttribute(fused_kernel, cudaFuncAttributeMaxDynamicSharedMemorySize, SMEM_BYTES);
  }
  Maps maps;
  const cuuint32_t es[3] = {1, 1, 1};
  auto map2 = [&](int i, CUtensorMapDataType t, const void* p, int d0, int d1, int bytes, int b0, int b1, CUtensorMapL2promotion pr) {
    cuuint64_t dims[2] = {(cuuint64_t)d0, (cuuint64_t)d1};
    cuuint64_t strides[1] = {(cuuint64_t)d0 * bytes};
    cuuint32_t box[2] = {(cuuint32_t)b0, (cuuint32_t)b1};
    enc(&maps.m[i], t, 2, (void*)p, dims, strides, box, es, CU_TENSOR_MAP_INTERLEAVE_NONE, CU_TENSOR_MAP_SWIZZLE_128B, pr, CU_TENSOR_MAP_FLOAT_OOB_FILL_NONE);
  };
  map2(M_XA, CU_TENSOR_MAP_DATA_TYPE_BFLOAT16, x, K_, M_, 2, BK, TA / 2, XPROM);
  map2(M_XC, CU_TENSOR_MAP_DATA_TYPE_BFLOAT16, x, K_, M_, 2, BK, TC - TA / 2, XPROM);
  map2(M_XD, CU_TENSOR_MAP_DATA_TYPE_BFLOAT16, x, K_, M_, 2, BK, TD - TB / 2, XPROM);
  map2(M_XB, CU_TENSOR_MAP_DATA_TYPE_BFLOAT16, x, K_, M_, 2, BK, TB / 2, XPROM);
  map2(M_O96, CU_TENSOR_MAP_DATA_TYPE_BFLOAT16, d_out, N_, M_, 2, 64, O24 ? 24 : 96, CU_TENSOR_MAP_L2_PROMOTION_NONE);
  map2(M_O32, CU_TENSOR_MAP_DATA_TYPE_BFLOAT16, d_out, N_, M_, 2, 64, OB, CU_TENSOR_MAP_L2_PROMOTION_NONE);
  map2(M_Q, CU_TENSOR_MAP_DATA_TYPE_INT32, qw, N_, K_, 4, 32, BK, QPROM);
  map2(M_W, CU_TENSOR_MAP_DATA_TYPE_BFLOAT16, gp + W_OFF, K_, N_ - 2048, 2, BK, 64, XPROM);
  {
    cuuint64_t dims[3] = {(cuuint64_t)N_, (cuuint64_t)K_ / 8, 8};
    cuuint64_t strides[2] = {(cuuint64_t)N_ * 32, (cuuint64_t)N_ * 4};
    cuuint32_t box[3] = {32, 16, 4};
    enc(&maps.m[M_Q2], CU_TENSOR_MAP_DATA_TYPE_INT32, 3, (void*)qw, dims, strides, box, es, CU_TENSOR_MAP_INTERLEAVE_NONE,
        CU_TENSOR_MAP_SWIZZLE_128B, QPROM, CU_TENSOR_MAP_FLOAT_OOB_FILL_NONE);
  }
  {
    cuuint64_t dims[3] = {32, (cuuint64_t)K_, (cuuint64_t)N_ / 32};
    cuuint64_t strides[2] = {(cuuint64_t)N_ * 4, 128};
    cuuint32_t box[3] = {32, 32, 4};
    enc(&maps.m[M_D], CU_TENSOR_MAP_DATA_TYPE_INT32, 3, (void*)qw, dims, strides, box, es, CU_TENSOR_MAP_INTERLEAVE_NONE,
        CU_TENSOR_MAP_SWIZZLE_128B, QPROM, CU_TENSOR_MAP_FLOAT_OOB_FILL_NONE);
  }
  maps.desc = (0x40000040ull << 32) + UD;
  for (int t = 0; t < 66; t++) {
    const int u = t - 32, g = t < 32 ? t & 7 : 1 + u % 7, j = t < 32 ? t >> 3 : 4 + u / 7;
    int cl = t >= 60 ? (int)((0x413B3F394035ull >> (8 * (t - 60))) & 0xff) : g == 7 ? 48 + 2 * j : g ? 6 * j + g - 1 : std::min(49 + 6 * j, 87 - 12 * j);
    if (GMAP == 0) cl = (t + 4) % 66;
    const int yi = cl / 6, fb = 2 * (cl % 6);
    const int fa = cl < 48 ? fb : 12 + 2 * (cl & 1), ta = cl < 48 ? TA * yi : std::min(TC * ((cl - 48) >> 1), M_ - TC);
    maps.tiles[t >= 62 ? t & 3 : t + 4] = fa | fb << 4 | ta << 5 | (TD * yi + (TB - TD) * std::max(yi - 8, 0)) << 13;
  }
  {
    int third[396], t2[396], nt = 0, na = 0;
    for (int i = 0; i < 396; i++) {
      const bool isb = (maps.tiles[i / 6] & 15) >= 12;
      third[i] = isb && i % 3 < NB3;
      t2[i] = 1;
      nt += third[i];
    }
    const int need = 104 - nt;
    for (int b = 0, k = 0; b < 132; b++) {
      if ((maps.tiles[b / 2] & 15) >= 12) continue;
      if ((na / 2 + 1) * need / 96 != (na / 2) * need / 96 || need >= 96) {
        third[3 * b] = 1;
        if (T2L == 0 && k >= need - 12) t2[3 * b] = 0;
        if (T2L == 1 && k < 12) t2[3 * b] = 0;
        k++;
      }
      na++;
    }
    if (NB3 == 0) for (int b = 131, k = 0; k < 8; b--) if ((maps.tiles[b / 2] & 15) >= 12) { third[3 * b] = 1; t2[3 * b] = 0; k++; }
    int u = 920, l = 0;
    for (int i = 0; i < 396; i++) maps.jobs[i] = third[i] ? u++ : 1024;
    std::pair<int, int> rd[396];
    for (int i = 0; i < 396; i++) rd[i] = {third[i] ? (int)maps.jobs[i] - 128 : 396 + U0(i / 3, i % 3), i};
    std::sort(rd, rd + 396);
    for (int k = 0; k < 396; k++) {
      const int i = rd[k].second;
      if (t2[i]) maps.jobs[i] |= l << 11 | std::min(LCAP, LT0 + l * LTS) / 8 << 20, l++;
      else maps.jobs[i] |= 384 << 11;
    }
  }
  fused_kernel<<<NUM_CTAS, NTHREADS, SMEM_BYTES, cudaStreamPerThread>>>(count, lut, gp, qw, (const uint8_t*)x, maps);
}
```

```cpp
#include <cuda_runtime.h>
#include <cuda_bf16.h>
#include <cuda.h>
#include <stdint.h>
#include <cstdio>
#include <algorithm>

namespace {

constexpr int M_ = 2048, K_ = 1024, N_ = 3584;
constexpr int BF = 128, BK = 64;
constexpr int TA = 256, TB = 192;
#define TCC 232
constexpr int TC = TCC, TD = 184;
constexpr int STAGES = 4;
constexpr int KBLKS = K_ / BK;
constexpr int X_BYTES = TA * BK * 2;
constexpr int UNIT_BYTES = BK * 32 * 4;
constexpr int SLAB_BYTES = BF * BK;
constexpr int STAGE_BYTES = X_BYTES + SLAB_BYTES;
constexpr int OFF_STG = STAGES * STAGE_BYTES;
constexpr int OFF_PL = OFF_STG + 3 * UNIT_BYTES;
constexpr int OFF_TAB = OFF_PL + 2048;
constexpr int OFF_BAR = OFF_STG + 65536;
constexpr int W_OFF = 16 * KBLKS * SLAB_BYTES;
constexpr int SMEM_BYTES = OFF_BAR + 512;
constexpr int NUM_CTAS = 132;
constexpr int NTHREADS = 384;
constexpr int NPACK = 3;
#define XT0 1400
#define WT0 2350
#define WTS 1000
#define S1D 400
#define PC 900
#define OB 32
#define WD 0x2212
#define RB 1
#define D0 600
#define WB 1
#define LT0 7800
#define LTS 15
#define XPROM CU_TENSOR_MAP_L2_PROMOTION_L2_128B
#define QPROM CU_TENSOR_MAP_L2_PROMOTION_L2_128B
#define S1B 1
#define S1N 15
#define NP 2
#define PN 16
#define EP1 1
#define W17 1
#define SB0 0
#define NSB 8
#define FEN 1
#define NSI 13
#define N88 1
#define GMAP 1
#define O24 1
#define EPW 1
#define LCAP 12300
#define NB3 1
#define T2L 1
#define ORD 1
#define PU 36
#define U0(r, p) (ORD == 0 ? 3 * (r) + (p) : ORD == 1 ? 132 * (p) + (r) : (p) ? 131 + 2 * (r) + (p) : (r))
#define G0 WT0
#define G1 (WT0 + WTS)
#define G2 (WT0 + 2 * WTS)
#define G3 (WT0 + 3 * WTS)
#define G4 (WT0 + 4 * WTS)
#define G5 (WT0 + 5 * WTS)
constexpr uint64_t GATES = (uint64_t)(G0 / 32) << 8 | (uint64_t)(G1 / 32) << 16 | (uint64_t)(G2 / 32) << 24 | (uint64_t)(G3 / 32) << 32 | (uint64_t)(G4 / 32) << 40 | (uint64_t)(G5 / 32) << 48;
#define TR1 1
#define TR2 1
#define SW 0
#define XPD 2
#define XPS 2
#define XPW 1
#define ONE 1
#define SHF 1
#define PLF 1
#define EXF 1
#define EFN 0
#define PF 8
#define LD0 1
#define LPS 2
#define FM 0x113c
#define QD 3
#define QN 8
#define NSH 2
static_assert(SMEM_BYTES <= 232448, "smem");
static_assert(TB * 128 + 2 * SLAB_BYTES == STAGE_BYTES, "stage");
constexpr int B_FULL = 0, B_EMPTY = 4, B_DIR = 8, B_SLOT = 9, NBARS = 12, B_LAST = 16, B_RDY = B_DIR;
constexpr int OFF_EPOCH = OFF_BAR + 8 * NBARS;
constexpr uint32_t SB = 1024;
constexpr uint32_t UD = (SB >> 4) | (1u << 16);
enum { M_Q, M_D, M_XA, M_XC, M_XB, M_XD, M_O96, M_O32, M_W, M_Q2, NMAPS };

__device__ __align__(1024) uint8_t g_p[W_OFF + 12 * KBLKS * 2 * SLAB_BYTES];
__device__ __align__(128) unsigned int g_count[32 * 97];

__device__ __forceinline__ uint32_t smem_u32(const void* p) { return (uint32_t)__cvta_generic_to_shared(p); }
__device__ __forceinline__ void mbar_init(uint32_t bar, uint32_t cnt) {
  asm volatile("mbarrier.init.shared::cta.b64 [%0], %1;" ::"r"(bar), "r"(cnt) : "memory");
}
__device__ __forceinline__ void mbar_wait(uint32_t bar, uint32_t parity, uint32_t& c) {
  asm volatile(
      "{\n.reg .pred p;\n"
      "SPIN:\n"
      "mbarrier.try_wait.parity.shared::cta.b64 p, [%1], %2;\n"
      "add.u32 %0, %0, 1;\n"
      "setp.ge.or.u32 p, %0, 0x100000, p;\n"
      "@!p bra.uni SPIN;\n}\n"
      : "+r"(c) : "r"(bar), "r"(parity) : "memory");
}
__device__ __forceinline__ void mbar_wait_fast(uint32_t bar, uint32_t parity, uint32_t& c) {
  asm volatile(
      "{\n.reg .pred p;\n"
      "SPIN:\n"
      "mbarrier.try_wait.parity.shared::cta.b64 p, [%1], %2;\n"
      "@p bra.uni DONE;\n"
      "add.u32 %0, %0, 1;\n"
      "setp.lt.u32 p, %0, 0x100000;\n"
      "@p bra.uni SPIN;\n"
      "DONE:\n}\n"
      : "+r"(c) : "r"(bar), "r"(parity) : "memory");
}
__device__ __forceinline__ bool mbar_test(uint32_t bar, uint32_t parity) {
  uint32_t ok;
  asm volatile("{\n.reg .pred p;\nmbarrier.try_wait.parity.shared::cta.b64 p, [%1], %2;\nselp.u32 %0, 1, 0, p;\n}\n" : "=r"(ok) : "r"(bar), "r"(parity) : "memory");
  return ok != 0;
}
__device__ __forceinline__ bool mbar_peek(uint32_t bar, uint32_t parity) {
  uint32_t ok;
  asm volatile("{\n.reg .pred p;\nmbarrier.test_wait.parity.shared::cta.b64 p, [%1], %2;\nselp.u32 %0, 1, 0, p;\n}\n" : "=r"(ok) : "r"(bar), "r"(parity) : "memory");
  return ok != 0;
}
__device__ __forceinline__ void mbar_arrive(uint32_t bar) {
  asm volatile("mbarrier.arrive.shared::cta.b64 _, [%0];" ::"r"(bar) : "memory");
}
__device__ __forceinline__ uint32_t mapa(uint32_t a, uint32_t cta) {
  uint32_t r;
  asm("mapa.shared::cluster.u32 %0, %1, %2;" : "=r"(r) : "r"(a), "r"(cta));
  return r;
}
__device__ __forceinline__ void mbar_arrive_remote_if(uint32_t ra, uint32_t cond) {
  asm volatile("{\n.reg .pred p;\nsetp.ne.u32 p, %1, 0;\n@p mbarrier.arrive.shared::cluster.b64 _, [%0];\n}\n" ::"r"(ra), "r"(cond) : "memory");
}
#define ELECT "{\n.reg .pred p;\nelect.sync _|p, 0xffffffff;\n"
__device__ __forceinline__ void expect_w(uint32_t bar, uint32_t bytes) {
  asm volatile(ELECT "@p mbarrier.arrive.expect_tx.shared::cta.b64 _, [%0], %1;\n}\n" ::"r"(bar), "r"(bytes) : "memory");
}
__device__ __forceinline__ void arrive_w(uint32_t bar) {
  asm volatile(ELECT "@p mbarrier.arrive.shared::cta.b64 _, [%0];\n}\n" ::"r"(bar) : "memory");
}
__device__ __forceinline__ void tma_mc_w(uint32_t dst, const CUtensorMap* map, uint32_t bar, int c0, int c1) {
  asm volatile(
      ELECT "@p cp.async.bulk.tensor.2d.shared::cluster.global.mbarrier::complete_tx::bytes.multicast::cluster [%0], [%1, {%3, %4}], [%2], %5;\n}\n"
      ::"r"(dst), "l"((uint64_t)map), "r"(bar), "r"(c0), "r"(c1), "h"((uint16_t)3) : "memory");
}
__device__ __forceinline__ void bulk_w(uint32_t dst, const void* src, uint32_t bytes, uint32_t bar) {
  asm volatile(ELECT "@p cp.async.bulk.shared::cluster.global.mbarrier::complete_tx::bytes [%0], [%1], %2, [%3];\n}\n"
               ::"r"(dst), "l"(src), "r"(bytes), "r"(bar) : "memory");
}
__device__ __forceinline__ void tma_w(uint32_t dst, const CUtensorMap* map, uint32_t bar, int c0, int c1) {
  asm volatile(
      ELECT "@p cp.async.bulk.tensor.2d.shared::cluster.global.mbarrier::complete_tx::bytes [%0], [%1, {%3, %4}], [%2];\n}\n"
      ::"r"(dst), "l"((uint64_t)map), "r"(bar), "r"(c0), "r"(c1) : "memory");
}
__device__ __forceinline__ void tma3_w(uint32_t dst, const CUtensorMap* map, uint32_t bar, int c0, int c1, int c2) {
  asm volatile(
      ELECT "@p cp.async.bulk.tensor.3d.shared::cluster.global.mbarrier::complete_tx::bytes [%0], [%1, {%3, %4, %5}], [%2];\n}\n"
      ::"r"(dst), "l"((uint64_t)map), "r"(bar), "r"(c0), "r"(c1), "r"(c2) : "memory");
}
__device__ __forceinline__ void store_w(const CUtensorMap* map, uint32_t src, int c0, int c1) {
  asm volatile(ELECT "@p cp.async.bulk.tensor.2d.global.shared::cta.bulk_group [%0, {%2, %3}], [%1];\n}\n"
               "cp.async.bulk.commit_group;"
               ::"l"((uint64_t)map), "r"(src), "r"(c0), "r"(c1) : "memory");
}
__device__ __forceinline__ void bulk_wait_read() { asm volatile("cp.async.bulk.wait_group.read 0;" ::: "memory"); }
__device__ __forceinline__ void cluster_arrive_relaxed() { asm volatile("barrier.cluster.arrive.relaxed.aligned;" ::: "memory"); }
__device__ __forceinline__ void cluster_wait() { asm volatile("barrier.cluster.wait.acquire.aligned;" ::: "memory"); }
__device__ __forceinline__ void wgmma_fence() { asm volatile("wgmma.fence.sync.aligned;" ::: "memory"); }
__device__ __forceinline__ void wgmma_commit() { asm volatile("wgmma.commit_group.sync.aligned;" ::: "memory"); }
template <int N> __device__ __forceinline__ void wgmma_wait() { asm volatile("wgmma.wait_group.sync.aligned %0;" ::"n"(N) : "memory"); }
template <int N> __device__ __forceinline__ void fence_regs(float (&p)[N]) {
#pragma unroll
  for (int i = 0; i < N; i++) asm volatile("" : "+f"(p[i]) :: "memory");
}

template <int N> __device__ __forceinline__ void wgmma_rs(float* d, const uint32_t* a, uint32_t descB, uint32_t accum);
template <> __device__ __forceinline__ void wgmma_rs<256>(float* d, const uint32_t* a, uint32_t descB, uint32_t accum) {
  asm volatile(
    "{\n.reg .pred p;\n.reg .b64 db;\n"
    "setp.ne.b32 p, %133, 0;\n"
    "mov.b64 db, {%132, 0x40000040};\n"
    "wgmma.mma_async.sync.aligned.m64n256k16.f32.bf16.bf16 "
    "{%0, %1, %2, %3, %4, %5, %6, %7, %8, %9, %10, %11, %12, %13, %14, %15, %16, %17, %18, %19, %20, %21, %22, %23, %24, %25, %26, %27, %28, %29, %30, %31, %32, %33, %34, %35, %36, %37, %38, %39, %40, %41, %42, %43, %44, %45, %46, %47, %48, %49, %50, %51, %52, %53, %54, %55, %56, %57, %58, %59, %60, %61, %62, %63, %64, %65, %66, %67, %68, %69, %70, %71, %72, %73, %74, %75, %76, %77, %78, %79, %80, %81, %82, %83, %84, %85, %86, %87, %88, %89, %90, %91, %92, %93, %94, %95, %96, %97, %98, %99, %100, %101, %102, %103, %104, %105, %106, %107, %108, %109, %110, %111, %112, %113, %114, %115, %116, %117, %118, %119, %120, %121, %122, %123, %124, %125, %126, %127}, "
    "{%128, %129, %130, %131}, db, p, 1, 1, 0;\n"
    "}\n"
    : "+f"(d[0]), "+f"(d[1]), "+f"(d[2]), "+f"(d[3]), "+f"(d[4]), "+f"(d[5]), "+f"(d[6]), "+f"(d[7]), "+f"(d[8]), "+f"(d[9]), "+f"(d[10]), "+f"(d[11]), "+f"(d[12]), "+f"(d[13]), "+f"(d[14]), "+f"(d[15]), "+f"(d[16]), "+f"(d[17]), "+f"(d[18]), "+f"(d[19]), "+f"(d[20]), "+f"(d[21]), "+f"(d[22]), "+f"(d[23]), "+f"(d[24]), "+f"(d[25]), "+f"(d[26]), "+f"(d[27]), "+f"(d[28]), "+f"(d[29]), "+f"(d[30]), "+f"(d[31]), "+f"(d[32]), "+f"(d[33]), "+f"(d[34]), "+f"(d[35]), "+f"(d[36]), "+f"(d[37]), "+f"(d[38]), "+f"(d[39]), "+f"(d[40]), "+f"(d[41]), "+f"(d[42]), "+f"(d[43]), "+f"(d[44]), "+f"(d[45]), "+f"(d[46]), "+f"(d[47]), "+f"(d[48]), "+f"(d[49]), "+f"(d[50]), "+f"(d[51]), "+f"(d[52]), "+f"(d[53]), "+f"(d[54]), "+f"(d[55]), "+f"(d[56]), "+f"(d[57]), "+f"(d[58]), "+f"(d[59]), "+f"(d[60]), "+f"(d[61]), "+f"(d[62]), "+f"(d[63]), "+f"(d[64]), "+f"(d[65]), "+f"(d[66]), "+f"(d[67]), "+f"(d[68]), "+f"(d[69]), "+f"(d[70]), "+f"(d[71]), "+f"(d[72]), "+f"(d[73]), "+f"(d[74]), "+f"(d[75]), "+f"(d[76]), "+f"(d[77]), "+f"(d[78]), "+f"(d[79]), "+f"(d[80]), "+f"(d[81]), "+f"(d[82]), "+f"(d[83]), "+f"(d[84]), "+f"(d[85]), "+f"(d[86]), "+f"(d[87]), "+f"(d[88]), "+f"(d[89]), "+f"(d[90]), "+f"(d[91]), "+f"(d[92]), "+f"(d[93]), "+f"(d[94]), "+f"(d[95]), "+f"(d[96]), "+f"(d[97]), "+f"(d[98]), "+f"(d[99]), "+f"(d[100]), "+f"(d[101]), "+f"(d[102]), "+f"(d[103]), "+f"(d[104]), "+f"(d[105]), "+f"(d[106]), "+f"(d[107]), "+f"(d[108]), "+f"(d[109]), "+f"(d[110]), "+f"(d[111]), "+f"(d[112]), "+f"(d[113]), "+f"(d[114]), "+f"(d[115]), "+f"(d[116]), "+f"(d[117]), "+f"(d[118]), "+f"(d[119]), "+f"(d[120]), "+f"(d[121]), "+f"(d[122]), "+f"(d[123]), "+f"(d[124]), "+f"(d[125]), "+f"(d[126]), "+f"(d[127])
    : "r"(a[0]), "r"(a[1]), "r"(a[2]), "r"(a[3]), "r"(descB), "r"(accum));
}
template <> __device__ __forceinline__ void wgmma_rs<232>(float* d, const uint32_t* a, uint32_t descB, uint32_t accum) {
  asm volatile(
    "{\n.reg .pred p;\n.reg .b64 db;\n"
    "setp.ne.b32 p, %121, 0;\n"
    "mov.b64 db, {%120, 0x40000040};\n"
    "wgmma.mma_async.sync.aligned.m64n232k16.f32.bf16.bf16 "
    "{%0, %1, %2, %3, %4, %5, %6, %7, %8, %9, %10, %11, %12, %13, %14, %15, %16, %17, %18, %19, %20, %21, %22, %23, %24, %25, %26, %27, %28, %29, %30, %31, %32, %33, %34, %35, %36, %37, %38, %39, %40, %41, %42, %43, %44, %45, %46, %47, %48, %49, %50, %51, %52, %53, %54, %55, %56, %57, %58, %59, %60, %61, %62, %63, %64, %65, %66, %67, %68, %69, %70, %71, %72, %73, %74, %75, %76, %77, %78, %79, %80, %81, %82, %83, %84, %85, %86, %87, %88, %89, %90, %91, %92, %93, %94, %95, %96, %97, %98, %99, %100, %101, %102, %103, %104, %105, %106, %107, %108, %109, %110, %111, %112, %113, %114, %115}, "
    "{%116, %117, %118, %119}, db, p, 1, 1, 0;\n"
    "}\n"
    : "+f"(d[0]), "+f"(d[1]), "+f"(d[2]), "+f"(d[3]), "+f"(d[4]), "+f"(d[5]), "+f"(d[6]), "+f"(d[7]), "+f"(d[8]), "+f"(d[9]), "+f"(d[10]), "+f"(d[11]), "+f"(d[12]), "+f"(d[13]), "+f"(d[14]), "+f"(d[15]), "+f"(d[16]), "+f"(d[17]), "+f"(d[18]), "+f"(d[19]), "+f"(d[20]), "+f"(d[21]), "+f"(d[22]), "+f"(d[23]), "+f"(d[24]), "+f"(d[25]), "+f"(d[26]), "+f"(d[27]), "+f"(d[28]), "+f"(d[29]), "+f"(d[30]), "+f"(d[31]), "+f"(d[32]), "+f"(d[33]), "+f"(d[34]), "+f"(d[35]), "+f"(d[36]), "+f"(d[37]), "+f"(d[38]), "+f"(d[39]), "+f"(d[40]), "+f"(d[41]), "+f"(d[42]), "+f"(d[43]), "+f"(d[44]), "+f"(d[45]), "+f"(d[46]), "+f"(d[47]), "+f"(d[48]), "+f"(d[49]), "+f"(d[50]), "+f"(d[51]), "+f"(d[52]), "+f"(d[53]), "+f"(d[54]), "+f"(d[55]), "+f"(d[56]), "+f"(d[57]), "+f"(d[58]), "+f"(d[59]), "+f"(d[60]), "+f"(d[61]), "+f"(d[62]), "+f"(d[63]), "+f"(d[64]), "+f"(d[65]), "+f"(d[66]), "+f"(d[67]), "+f"(d[68]), "+f"(d[69]), "+f"(d[70]), "+f"(d[71]), "+f"(d[72]), "+f"(d[73]), "+f"(d[74]), "+f"(d[75]), "+f"(d[76]), "+f"(d[77]), "+f"(d[78]), "+f"(d[79]), "+f"(d[80]), "+f"(d[81]), "+f"(d[82]), "+f"(d[83]), "+f"(d[84]), "+f"(d[85]), "+f"(d[86]), "+f"(d[87]), "+f"(d[88]), "+f"(d[89]), "+f"(d[90]), "+f"(d[91]), "+f"(d[92]), "+f"(d[93]), "+f"(d[94]), "+f"(d[95]), "+f"(d[96]), "+f"(d[97]), "+f"(d[98]), "+f"(d[99]), "+f"(d[100]), "+f"(d[101]), "+f"(d[102]), "+f"(d[103]), "+f"(d[104]), "+f"(d[105]), "+f"(d[106]), "+f"(d[107]), "+f"(d[108]), "+f"(d[109]), "+f"(d[110]), "+f"(d[111]), "+f"(d[112]), "+f"(d[113]), "+f"(d[114]), "+f"(d[115])
    : "r"(a[0]), "r"(a[1]), "r"(a[2]), "r"(a[3]), "r"(descB), "r"(accum));
}
template <> __device__ __forceinline__ void wgmma_rs<192>(float* d, const uint32_t* a, uint32_t descB, uint32_t accum) {
  asm volatile(
    "{\n.reg .pred p;\n.reg .b64 db;\n"
    "setp.ne.b32 p, %101, 0;\n"
    "mov.b64 db, {%100, 0x40000040};\n"
    "wgmma.mma_async.sync.aligned.m64n192k16.f32.bf16.bf16 "
    "{%0, %1, %2, %3, %4, %5, %6, %7, %8, %9, %10, %11, %12, %13, %14, %15, %16, %17, %18, %19, %20, %21, %22, %23, %24, %25, %26, %27, %28, %29, %30, %31, %32, %33, %34, %35, %36, %37, %38, %39, %40, %41, %42, %43, %44, %45, %46, %47, %48, %49, %50, %51, %52, %53, %54, %55, %56, %57, %58, %59, %60, %61, %62, %63, %64, %65, %66, %67, %68, %69, %70, %71, %72, %73, %74, %75, %76, %77, %78, %79, %80, %81, %82, %83, %84, %85, %86, %87, %88, %89, %90, %91, %92, %93, %94, %95}, "
    "{%96, %97, %98, %99}, db, p, 1, 1, 0;\n"
    "}\n"
    : "+f"(d[0]), "+f"(d[1]), "+f"(d[2]), "+f"(d[3]), "+f"(d[4]), "+f"(d[5]), "+f"(d[6]), "+f"(d[7]), "+f"(d[8]), "+f"(d[9]), "+f"(d[10]), "+f"(d[11]), "+f"(d[12]), "+f"(d[13]), "+f"(d[14]), "+f"(d[15]), "+f"(d[16]), "+f"(d[17]), "+f"(d[18]), "+f"(d[19]), "+f"(d[20]), "+f"(d[21]), "+f"(d[22]), "+f"(d[23]), "+f"(d[24]), "+f"(d[25]), "+f"(d[26]), "+f"(d[27]), "+f"(d[28]), "+f"(d[29]), "+f"(d[30]), "+f"(d[31]), "+f"(d[32]), "+f"(d[33]), "+f"(d[34]), "+f"(d[35]), "+f"(d[36]), "+f"(d[37]), "+f"(d[38]), "+f"(d[39]), "+f"(d[40]), "+f"(d[41]), "+f"(d[42]), "+f"(d[43]), "+f"(d[44]), "+f"(d[45]), "+f"(d[46]), "+f"(d[47]), "+f"(d[48]), "+f"(d[49]), "+f"(d[50]), "+f"(d[51]), "+f"(d[52]), "+f"(d[53]), "+f"(d[54]), "+f"(d[55]), "+f"(d[56]), "+f"(d[57]), "+f"(d[58]), "+f"(d[59]), "+f"(d[60]), "+f"(d[61]), "+f"(d[62]), "+f"(d[63]), "+f"(d[64]), "+f"(d[65]), "+f"(d[66]), "+f"(d[67]), "+f"(d[68]), "+f"(d[69]), "+f"(d[70]), "+f"(d[71]), "+f"(d[72]), "+f"(d[73]), "+f"(d[74]), "+f"(d[75]), "+f"(d[76]), "+f"(d[77]), "+f"(d[78]), "+f"(d[79]), "+f"(d[80]), "+f"(d[81]), "+f"(d[82]), "+f"(d[83]), "+f"(d[84]), "+f"(d[85]), "+f"(d[86]), "+f"(d[87]), "+f"(d[88]), "+f"(d[89]), "+f"(d[90]), "+f"(d[91]), "+f"(d[92]), "+f"(d[93]), "+f"(d[94]), "+f"(d[95])
    : "r"(a[0]), "r"(a[1]), "r"(a[2]), "r"(a[3]), "r"(descB), "r"(accum));
}
template <> __device__ __forceinline__ void wgmma_rs<88>(float* d, const uint32_t* a, uint32_t descB, uint32_t accum) {
  asm volatile(
    "{\n.reg .pred p;\n.reg .b64 db;\n"
    "setp.ne.b32 p, %49, 0;\n"
    "mov.b64 db, {%48, 0x40000040};\n"
    "wgmma.mma_async.sync.aligned.m64n88k16.f32.bf16.bf16 "
    "{%0, %1, %2, %3, %4, %5, %6, %7, %8, %9, %10, %11, %12, %13, %14, %15, %16, %17, %18, %19, %20, %21, %22, %23, %24, %25, %26, %27, %28, %29, %30, %31, %32, %33, %34, %35, %36, %37, %38, %39, %40, %41, %42, %43}, "
    "{%44, %45, %46, %47}, db, p, 1, 1, 0;\n"
    "}\n"
    : "+f"(d[0]), "+f"(d[1]), "+f"(d[2]), "+f"(d[3]), "+f"(d[4]), "+f"(d[5]), "+f"(d[6]), "+f"(d[7]), "+f"(d[8]), "+f"(d[9]), "+f"(d[10]), "+f"(d[11]), "+f"(d[12]), "+f"(d[13]), "+f"(d[14]), "+f"(d[15]), "+f"(d[16]), "+f"(d[17]), "+f"(d[18]), "+f"(d[19]), "+f"(d[20]), "+f"(d[21]), "+f"(d[22]), "+f"(d[23]), "+f"(d[24]), "+f"(d[25]), "+f"(d[26]), "+f"(d[27]), "+f"(d[28]), "+f"(d[29]), "+f"(d[30]), "+f"(d[31]), "+f"(d[32]), "+f"(d[33]), "+f"(d[34]), "+f"(d[35]), "+f"(d[36]), "+f"(d[37]), "+f"(d[38]), "+f"(d[39]), "+f"(d[40]), "+f"(d[41]), "+f"(d[42]), "+f"(d[43])
    : "r"(a[0]), "r"(a[1]), "r"(a[2]), "r"(a[3]), "r"(descB), "r"(accum));
}
template <> __device__ __forceinline__ void wgmma_rs<64>(float* d, const uint32_t* a, uint32_t descB, uint32_t accum) {
  asm volatile(
    "{\n.reg .pred p;\n.reg .b64 db;\n"
    "setp.ne.b32 p, %37, 0;\n"
    "mov.b64 db, {%36, 0x40000040};\n"
    "wgmma.mma_async.sync.aligned.m64n64k16.f32.bf16.bf16 "
    "{%0, %1, %2, %3, %4, %5, %6, %7, %8, %9, %10, %11, %12, %13, %14, %15, %16, %17, %18, %19, %20, %21, %22, %23, %24, %25, %26, %27, %28, %29, %30, %31}, "
    "{%32, %33, %34, %35}, db, p, 1, 1, 0;\n"
    "}\n"
    : "+f"(d[0]), "+f"(d[1]), "+f"(d[2]), "+f"(d[3]), "+f"(d[4]), "+f"(d[5]), "+f"(d[6]), "+f"(d[7]), "+f"(d[8]), "+f"(d[9]), "+f"(d[10]), "+f"(d[11]), "+f"(d[12]), "+f"(d[13]), "+f"(d[14]), "+f"(d[15]), "+f"(d[16]), "+f"(d[17]), "+f"(d[18]), "+f"(d[19]), "+f"(d[20]), "+f"(d[21]), "+f"(d[22]), "+f"(d[23]), "+f"(d[24]), "+f"(d[25]), "+f"(d[26]), "+f"(d[27]), "+f"(d[28]), "+f"(d[29]), "+f"(d[30]), "+f"(d[31])
    : "r"(a[0]), "r"(a[1]), "r"(a[2]), "r"(a[3]), "r"(descB), "r"(accum));
}
template <> __device__ __forceinline__ void wgmma_rs<40>(float* d, const uint32_t* a, uint32_t descB, uint32_t accum) {
  asm volatile(
    "{\n.reg .pred p;\n.reg .b64 db;\n"
    "setp.ne.b32 p, %25, 0;\n"
    "mov.b64 db, {%24, 0x40000040};\n"
    "wgmma.mma_async.sync.aligned.m64n40k16.f32.bf16.bf16 "
    "{%0, %1, %2, %3, %4, %5, %6, %7, %8, %9, %10, %11, %12, %13, %14, %15, %16, %17, %18, %19}, "
    "{%20, %21, %22, %23}, db, p, 1, 1, 0;\n"
    "}\n"
    : "+f"(d[0]), "+f"(d[1]), "+f"(d[2]), "+f"(d[3]), "+f"(d[4]), "+f"(d[5]), "+f"(d[6]), "+f"(d[7]), "+f"(d[8]), "+f"(d[9]), "+f"(d[10]), "+f"(d[11]), "+f"(d[12]), "+f"(d[13]), "+f"(d[14]), "+f"(d[15]), "+f"(d[16]), "+f"(d[17]), "+f"(d[18]), "+f"(d[19])
    : "r"(a[0]), "r"(a[1]), "r"(a[2]), "r"(a[3]), "r"(descB), "r"(accum));
}

template <int N> __device__ __forceinline__ void wgmma_rl(float* d, const uint32_t* a, uint64_t descB);
template <> __device__ __forceinline__ void wgmma_rl<96>(float* d, const uint32_t* a, uint64_t descB) {
  asm volatile(
    "wgmma.mma_async.sync.aligned.m64n96k16.f32.bf16.bf16 "
    "{%0, %1, %2, %3, %4, %5, %6, %7, %8, %9, %10, %11, %12, %13, %14, %15, %16, %17, %18, %19, %20, %21, %22, %23, %24, %25, %26, %27, %28, %29, %30, %31, %32, %33, %34, %35, %36, %37, %38, %39, %40, %41, %42, %43, %44, %45, %46, %47}, "
    "{%48, %49, %50, %51}, %52, 1, 1, 1, 0;\n"
    : "+f"(d[0]), "+f"(d[1]), "+f"(d[2]), "+f"(d[3]), "+f"(d[4]), "+f"(d[5]), "+f"(d[6]), "+f"(d[7]), "+f"(d[8]), "+f"(d[9]), "+f"(d[10]), "+f"(d[11]), "+f"(d[12]), "+f"(d[13]), "+f"(d[14]), "+f"(d[15]), "+f"(d[16]), "+f"(d[17]), "+f"(d[18]), "+f"(d[19]), "+f"(d[20]), "+f"(d[21]), "+f"(d[22]), "+f"(d[23]), "+f"(d[24]), "+f"(d[25]), "+f"(d[26]), "+f"(d[27]), "+f"(d[28]), "+f"(d[29]), "+f"(d[30]), "+f"(d[31]), "+f"(d[32]), "+f"(d[33]), "+f"(d[34]), "+f"(d[35]), "+f"(d[36]), "+f"(d[37]), "+f"(d[38]), "+f"(d[39]), "+f"(d[40]), "+f"(d[41]), "+f"(d[42]), "+f"(d[43]), "+f"(d[44]), "+f"(d[45]), "+f"(d[46]), "+f"(d[47])
    : "r"(a[0]), "r"(a[1]), "r"(a[2]), "r"(a[3]), "l"(descB));
}

template <int N> __device__ __forceinline__ void wgmma_ss(float* d, uint64_t descA, uint64_t descB, uint32_t accum);
template <> __device__ __forceinline__ void wgmma_ss<192>(float* d, uint64_t descA, uint64_t descB, uint32_t accum) {
  asm volatile(
    "{\n.reg .pred p;\n"
    "setp.ne.b32 p, %98, 0;\n"
    "wgmma.mma_async.sync.aligned.m64n192k16.f32.bf16.bf16 "
    "{%0, %1, %2, %3, %4, %5, %6, %7, %8, %9, %10, %11, %12, %13, %14, %15, %16, %17, %18, %19, %20, %21, %22, %23, %24, %25, %26, %27, %28, %29, %30, %31, %32, %33, %34, %35, %36, %37, %38, %39, %40, %41, %42, %43, %44, %45, %46, %47, %48, %49, %50, %51, %52, %53, %54, %55, %56, %57, %58, %59, %60, %61, %62, %63, %64, %65, %66, %67, %68, %69, %70, %71, %72, %73, %74, %75, %76, %77, %78, %79, %80, %81, %82, %83, %84, %85, %86, %87, %88, %89, %90, %91, %92, %93, %94, %95}, "
    "%96, %97, p, 1, 1, 0, 0;\n"
    "}\n"
    : "+f"(d[0]), "+f"(d[1]), "+f"(d[2]), "+f"(d[3]), "+f"(d[4]), "+f"(d[5]), "+f"(d[6]), "+f"(d[7]), "+f"(d[8]), "+f"(d[9]), "+f"(d[10]), "+f"(d[11]), "+f"(d[12]), "+f"(d[13]), "+f"(d[14]), "+f"(d[15]), "+f"(d[16]), "+f"(d[17]), "+f"(d[18]), "+f"(d[19]), "+f"(d[20]), "+f"(d[21]), "+f"(d[22]), "+f"(d[23]), "+f"(d[24]), "+f"(d[25]), "+f"(d[26]), "+f"(d[27]), "+f"(d[28]), "+f"(d[29]), "+f"(d[30]), "+f"(d[31]), "+f"(d[32]), "+f"(d[33]), "+f"(d[34]), "+f"(d[35]), "+f"(d[36]), "+f"(d[37]), "+f"(d[38]), "+f"(d[39]), "+f"(d[40]), "+f"(d[41]), "+f"(d[42]), "+f"(d[43]), "+f"(d[44]), "+f"(d[45]), "+f"(d[46]), "+f"(d[47]), "+f"(d[48]), "+f"(d[49]), "+f"(d[50]), "+f"(d[51]), "+f"(d[52]), "+f"(d[53]), "+f"(d[54]), "+f"(d[55]), "+f"(d[56]), "+f"(d[57]), "+f"(d[58]), "+f"(d[59]), "+f"(d[60]), "+f"(d[61]), "+f"(d[62]), "+f"(d[63]), "+f"(d[64]), "+f"(d[65]), "+f"(d[66]), "+f"(d[67]), "+f"(d[68]), "+f"(d[69]), "+f"(d[70]), "+f"(d[71]), "+f"(d[72]), "+f"(d[73]), "+f"(d[74]), "+f"(d[75]), "+f"(d[76]), "+f"(d[77]), "+f"(d[78]), "+f"(d[79]), "+f"(d[80]), "+f"(d[81]), "+f"(d[82]), "+f"(d[83]), "+f"(d[84]), "+f"(d[85]), "+f"(d[86]), "+f"(d[87]), "+f"(d[88]), "+f"(d[89]), "+f"(d[90]), "+f"(d[91]), "+f"(d[92]), "+f"(d[93]), "+f"(d[94]), "+f"(d[95])
    : "l"(descA), "l"(descB), "r"(accum));
}
template <> __device__ __forceinline__ void wgmma_ss<184>(float* d, uint64_t descA, uint64_t descB, uint32_t accum) {
  asm volatile(
    "{\n.reg .pred p;\n"
    "setp.ne.b32 p, %94, 0;\n"
    "wgmma.mma_async.sync.aligned.m64n184k16.f32.bf16.bf16 "
    "{%0, %1, %2, %3, %4, %5, %6, %7, %8, %9, %10, %11, %12, %13, %14, %15, %16, %17, %18, %19, %20, %21, %22, %23, %24, %25, %26, %27, %28, %29, %30, %31, %32, %33, %34, %35, %36, %37, %38, %39, %40, %41, %42, %43, %44, %45, %46, %47, %48, %49, %50, %51, %52, %53, %54, %55, %56, %57, %58, %59, %60, %61, %62, %63, %64, %65, %66, %67, %68, %69, %70, %71, %72, %73, %74, %75, %76, %77, %78, %79, %80, %81, %82, %83, %84, %85, %86, %87, %88, %89, %90, %91}, "
    "%92, %93, p, 1, 1, 0, 0;\n"
    "}\n"
    : "+f"(d[0]), "+f"(d[1]), "+f"(d[2]), "+f"(d[3]), "+f"(d[4]), "+f"(d[5]), "+f"(d[6]), "+f"(d[7]), "+f"(d[8]), "+f"(d[9]), "+f"(d[10]), "+f"(d[11]), "+f"(d[12]), "+f"(d[13]), "+f"(d[14]), "+f"(d[15]), "+f"(d[16]), "+f"(d[17]), "+f"(d[18]), "+f"(d[19]), "+f"(d[20]), "+f"(d[21]), "+f"(d[22]), "+f"(d[23]), "+f"(d[24]), "+f"(d[25]), "+f"(d[26]), "+f"(d[27]), "+f"(d[28]), "+f"(d[29]), "+f"(d[30]), "+f"(d[31]), "+f"(d[32]), "+f"(d[33]), "+f"(d[34]), "+f"(d[35]), "+f"(d[36]), "+f"(d[37]), "+f"(d[38]), "+f"(d[39]), "+f"(d[40]), "+f"(d[41]), "+f"(d[42]), "+f"(d[43]), "+f"(d[44]), "+f"(d[45]), "+f"(d[46]), "+f"(d[47]), "+f"(d[48]), "+f"(d[49]), "+f"(d[50]), "+f"(d[51]), "+f"(d[52]), "+f"(d[53]), "+f"(d[54]), "+f"(d[55]), "+f"(d[56]), "+f"(d[57]), "+f"(d[58]), "+f"(d[59]), "+f"(d[60]), "+f"(d[61]), "+f"(d[62]), "+f"(d[63]), "+f"(d[64]), "+f"(d[65]), "+f"(d[66]), "+f"(d[67]), "+f"(d[68]), "+f"(d[69]), "+f"(d[70]), "+f"(d[71]), "+f"(d[72]), "+f"(d[73]), "+f"(d[74]), "+f"(d[75]), "+f"(d[76]), "+f"(d[77]), "+f"(d[78]), "+f"(d[79]), "+f"(d[80]), "+f"(d[81]), "+f"(d[82]), "+f"(d[83]), "+f"(d[84]), "+f"(d[85]), "+f"(d[86]), "+f"(d[87]), "+f"(d[88]), "+f"(d[89]), "+f"(d[90]), "+f"(d[91])
    : "l"(descA), "l"(descB), "r"(accum));
}

template <int N> struct IC { static constexpr int v = N; };

__device__ __forceinline__ void stmatrix_x4_t(uint32_t addr, uint32_t r0, uint32_t r1, uint32_t r2, uint32_t r3) {
  asm volatile("stmatrix.sync.aligned.m8n8.x4.trans.shared.b16 [%0], {%1, %2, %3, %4};"
               ::"r"(addr), "r"(r0), "r"(r1), "r"(r2), "r"(r3) : "memory");
}
__device__ __forceinline__ void ldmatrix_x4(uint32_t* r, uint32_t addr) {
  asm volatile("ldmatrix.sync.aligned.m8n8.x4.shared.b16 {%0, %1, %2, %3}, [%4];"
               : "=r"(r[0]), "=r"(r[1]), "=r"(r[2]), "=r"(r[3]) : "r"(addr) : "memory");
}
__device__ __forceinline__ uint32_t pack_bf16(float a, float b) {
  __nv_bfloat162 v = __floats2bfloat162_rn(a, b);
  return *reinterpret_cast<uint32_t*>(&v);
}
__device__ __forceinline__ uint32_t prmt(uint32_t a, uint32_t b, uint32_t s) {
  uint32_t d;
  asm("prmt.b32 %0, %1, %2, %3;" : "=r"(d) : "r"(a), "r"(b), "r"(s));
  return d;
}
__device__ __forceinline__ uint32_t lds32(uint32_t a) {
  uint32_t v;
  asm volatile("ld.shared.u32 %0, [%1];" : "=r"(v) : "r"(a) : "memory");
  return v;
}
__device__ __forceinline__ void lds128(uint32_t* v, uint32_t a) {
  asm volatile("ld.shared.v4.u32 {%0, %1, %2, %3}, [%4];" : "=r"(v[0]), "=r"(v[1]), "=r"(v[2]), "=r"(v[3]) : "r"(a) : "memory");
}
__device__ __forceinline__ void sts128(uint32_t a, const uint32_t* v) {
  asm volatile("st.shared.v4.u32 [%0], {%1, %2, %3, %4};" ::"r"(a), "r"(v[0]), "r"(v[1]), "r"(v[2]), "r"(v[3]) : "memory");
}
__device__ __forceinline__ void sts32(uint32_t a, uint32_t v) {
  asm volatile("st.shared.u32 [%0], %1;" ::"r"(a), "r"(v) : "memory");
}
__device__ __forceinline__ void wait_until(uint32_t t0, uint32_t at) {
  asm volatile(
      "{\n.reg .pred p;\n.reg .s32 r;\n"
      "SPIN:\n"
      "mov.u32 r, %%clock;\n"
      "sub.s32 r, %0, r;\n"
      "setp.gt.s32 p, r, 0;\n"
      "shr.s32 r, r, %1;\n"
      "@p nanosleep.u32 r;\n"
      "@p bra.uni SPIN;\n}\n"
      ::"r"(t0 + at), "n"(NSH) : "memory");
}
__device__ __forceinline__ void spin_until(uint32_t t0, uint32_t at) {
  while ((uint32_t)clock() - t0 < at) {}
}
__device__ __forceinline__ void wait_count(const unsigned int* f, uint32_t& c) {
  asm volatile(
      "{\n.reg .pred p;\n.reg .u32 v;\n"
      "SPIN:\n"
      "ld.acquire.gpu.global.u32 v, [%1];\n"
      "add.u32 %0, %0, 16;\n"
      "setp.lt.u32 p, %0, 0x100000;\n"
      "setp.lt.and.u32 p, v, 64, p;\n"
      "@p nanosleep.u32 100;\n"
      "@p bra.uni SPIN;\n}\n"
      : "+r"(c) : "l"(f) : "memory");
}
template <int E>
__device__ __forceinline__ void ld_lut(uint32_t* v, const __nv_bfloat16* p) {
  asm volatile("ld.global.nc.u32 %0, [%1+%2];" : "=r"(v[E]) : "l"(p), "n"(((E & 3) * N_ + 8 * (E >> 2)) * 2));
  if constexpr (E < 7) ld_lut<E + 1>(v, p);
}
template <int OFF>
__device__ __forceinline__ void ld_codes4(uint32_t* w, const int* p) {
  asm volatile("ld.global.nc.L1::no_allocate.v4.u32 {%0, %1, %2, %3}, [%4+%5];" : "=r"(w[0]), "=r"(w[1]), "=r"(w[2]), "=r"(w[3]) : "l"(p), "n"(OFF));
}
__device__ __forceinline__ void ld_codes(uint32_t* w, const int* p) {
  ld_codes4<0>(w, p);
  ld_codes4<N_ * 4>(w + 4, p);
  ld_codes4<N_ * 32>(w + 8, p);
  ld_codes4<N_ * 36>(w + 12, p);
}
__device__ __forceinline__ void prefetch_map(const CUtensorMap* map) {
  asm volatile("prefetch.tensormap [%0];" ::"l"((uint64_t)map) : "memory");
}
template <int OFF>
__device__ __forceinline__ void ld_words(uint32_t* w, const uint8_t* p) {
  asm volatile("ld.relaxed.gpu.global.v4.u32 {%0, %1, %2, %3}, [%4+%5];" : "=r"(w[0]), "=r"(w[1]), "=r"(w[2]), "=r"(w[3]) : "l"(p), "n"(OFF) : "memory");
}
template <int OFF>
__device__ __forceinline__ void st_words(uint8_t* p, const uint32_t* w) {
  asm volatile("st.relaxed.gpu.global.v4.u32 [%0+%5], {%1, %2, %3, %4};" ::"l"(p), "r"(w[0]), "r"(w[1]), "r"(w[2]), "r"(w[3]), "n"(OFF) : "memory");
}

#define DBGR(i, j)
#define DBG(i)

__device__ __forceinline__ uint32_t word_key(uint32_t odd) { return 0xcdf00000u + (odd << 19); }
__device__ __forceinline__ uint32_t make_word(uint32_t c0, uint32_t c1, uint32_t c2, uint32_t c3, uint32_t key) {
  uint32_t p01, p23, n, w;
  asm("mad.lo.u32 %0, %1, 16, %2;" : "=r"(p01) : "r"(c1), "r"(c0));
  asm("mad.lo.u32 %0, %1, 16, %2;" : "=r"(p23) : "r"(c3), "r"(c2));
  asm("mad.lo.u32 %0, %1, 256, %2;" : "=r"(n) : "r"(p23), "r"(p01));
  asm("mad.lo.u32 %0, %1, 0x7fff, %2;" : "=r"(w) : "r"((n & 0x8888u) | key), "r"(n));
  return w;
}
struct Planes { uint32_t v[4][4]; };
__device__ __forceinline__ void lookup4(const Planes& pl, int c, uint32_t s, uint32_t sc, uint32_t& o0, uint32_t& o1) {
  uint32_t s2;
  asm("{\n.reg .b16 l, h;\n.reg .b32 t;\nmov.b32 {l, h}, %1;\nmov.b32 t, {h, h};\nmul.rn.f16x2 %0, t, %2;\n}\n" : "=r"(s2) : "r"(s), "r"(sc));
  const uint32_t lo = prmt(prmt(pl.v[0][2 * c], pl.v[1][2 * c], s), prmt(pl.v[2][2 * c], pl.v[3][2 * c], s), s2);
  const uint32_t hi = prmt(prmt(pl.v[0][2 * c + 1], pl.v[1][2 * c + 1], s), prmt(pl.v[2][2 * c + 1], pl.v[3][2 * c + 1], s), s2);
  o0 = prmt(lo, hi, 0x5140);
  o1 = prmt(lo, hi, 0x7362);
}
__device__ __forceinline__ void store_planes(uint32_t dst, const uint32_t* lv) {
#pragma unroll
  for (int h = 0; h < 2; h++) {
    uint32_t qp[4];
#pragma unroll
    for (int c = 0; c < 2; c++) {
      const uint32_t a = prmt(lv[4 * c], lv[4 * c + 1], h ? 0x7362 : 0x5140), b = prmt(lv[4 * c + 2], lv[4 * c + 3], h ? 0x7362 : 0x5140);
      qp[2 * c] = prmt(a, b, 0x5410);
      qp[2 * c + 1] = prmt(a, b, 0x7632);
    }
    sts128(dst + 64 * h, qp);
  }
}
__device__ __forceinline__ bool words_ok(const uint32_t* P, uint32_t tag) {
  return (P[0] & P[1] & P[2] & P[3] & P[4] & P[5] & P[6] & P[7] & tag) != 0;
}
template <int NJ>
__device__ __forceinline__ void stage_part(const float* a, uint32_t sts) {
#pragma unroll
  for (int j = 0; j < NJ; j++)
    stmatrix_x4_t(sts + 16 * j * 128, pack_bf16(a[8 * j], a[8 * j + 1]), pack_bf16(a[8 * j + 2], a[8 * j + 3]),
                  pack_bf16(a[8 * j + 4], a[8 * j + 5]), pack_bf16(a[8 * j + 6], a[8 * j + 7]));
}

template <int OFF>
__device__ __forceinline__ uint32_t lut_at(uint32_t tab, uint32_t c) {
  uint32_t v;
  asm volatile("ld.shared.u16 %0, [%1+%2];" : "=r"(v) : "r"(tab + 40 * c), "n"(OFF));
  return v;
}
template <int J>
__device__ __forceinline__ void convert_col(const uint32_t (*v)[4], uint32_t tab, uint8_t* dst) {
  uint32_t o[4];
#pragma unroll
  for (int i = 0; i < 4; i++) {
    const uint32_t a = lut_at<2 * J>(tab, v[2 * i][J]), b = lut_at<2 * J>(tab, v[2 * i + 1][J]);
    asm("mad.lo.u32 %0, %1, 65536, %2;" : "=r"(o[i]) : "r"(b), "r"(a));
  }
  st_words<2048 * J>(dst, o);
}

template <int J>
__device__ __forceinline__ void convert_shfl(const uint32_t (*v)[4], uint32_t e, uint8_t* dst) {
  uint32_t o[4];
#pragma unroll
  for (int i = 0; i < 4; i++) {
    uint32_t a, b;
    asm volatile("shfl.sync.idx.b32 %0, %1, %2, 0x101f, 0xffffffff;" : "=r"(a) : "r"(e), "r"(v[2 * i][J]));
    asm volatile("shfl.sync.idx.b32 %0, %1, %2, 0x101f, 0xffffffff;" : "=r"(b) : "r"(e), "r"(v[2 * i + 1][J]));
    o[i] = prmt(a, b, J & 1 ? 0x7632 : 0x5410);
  }
  st_words<2048 * J>(dst, o);
}

struct Maps { CUtensorMap m[NMAPS]; uint64_t desc; uint32_t tiles[66], jobs[396]; };
#define TILES() \
  const int fta = (te & 15) + rank, ftb = ((te >> 4) & 15) + rank, toka = (te >> 5) & 0x7f8, tokb = (te >> 13) & 0x7f8; \
  const bool big = fta < 12; \
  (void)toka; (void)big; (void)tokb
__global__ void __cluster_dims__(2, 1, 1) __launch_bounds__(NTHREADS, 1)
fused_kernel(unsigned int* __restrict__ count, const __nv_bfloat16* __restrict__ lut, uint8_t* __restrict__ gp,
             const int* __restrict__ qw, const uint8_t* __restrict__ xg, const __grid_constant__ Maps maps) {
  extern __shared__ __align__(1024) uint8_t smem_gen[];
  const uint32_t t0 = clock();
  const int tid = threadIdx.x;
  uint32_t cf[16];
  const int* src = qw + (((tid >> 8) * BK + 32 + (tid & 48) + ((tid >> 1) & 6)) * N_ + (blockIdx.x & 127) * 16 + (tid & 3) * 4);
  uint32_t ep0 = 0;
  if ((tid >> 6) == 2) {
    if (EPW) asm volatile("ld.relaxed.gpu.global.u32 %0, [%1];" : "=r"(ep0) : "l"(count) : "memory");
    ld_codes(cf, src);
  }
  const uint32_t te = maps.tiles[blockIdx.x >> 1];
  const int rank = blockIdx.x & 1;
  const uint32_t sl = smem_u32(smem_gen);
  auto bar = [&](int i) { return sl + OFF_BAR + 8 * i; };
  const int w12 = __shfl_sync(0xffffffffu, tid >> 5, 0);
  const int wg = w12 >> 2;
  const int warp = w12 & 3;
  const int lane = tid & 31;
  uint32_t bud = 0;
  if (__builtin_expect(wg == 0, 1)) {
    asm volatile("setmaxnreg.dec.sync.aligned.u32 72;");
    if (warp == 0) {
      if (lane == 0) {
#pragma unroll
        for (int i = 0; i < NBARS; i++) mbar_init(bar(i), i >= 4 && i < 8 ? 4 : 1);
        mbar_init(bar(B_LAST), 4);
        asm volatile("fence.mbarrier_init.release.cluster;" ::: "memory");
      }
      __syncwarp();
      cluster_arrive_relaxed();
      asm volatile("bar.arrive 4, 128;" ::: "memory");
      DBG(1);
      TILES();
      expect_w(bar(B_DIR), 2 * UNIT_BYTES);
      tma3_w(sl + 3 * STAGE_BYTES, &maps.m[M_D], bar(B_DIR), 0, 0, fta * 4);
      const int ca = TR1 && !big ? (TA - TC) * 128 : 0, cb = TR2 && big ? (TB - TD) * 128 : 0;
      const CUtensorMap *ma = &maps.m[M_XA + (ca ? rank : 0)], *mb = &maps.m[M_XB + (cb ? rank : 0)];
      expect_w(bar(B_FULL), X_BYTES - ca);
      cluster_wait();
      tma_mc_w(sl + rank * (X_BYTES / 2), ma, bar(B_FULL), 0, toka + rank * (TA / 2));
      DBG(2);
      expect_w(bar(B_LAST), SLAB_BYTES);
      wait_until(t0, XT0);
#pragma unroll 1
      for (int n = 1; n < 2 * KBLKS - 4; n++) {
        const int stage = n & 3;
        const bool first = n < KBLKS;
        const int rows = rank * (first ? TA / 2 : TB / 2);
        if (EXF) expect_w(bar(B_FULL + stage), STAGE_BYTES - (first ? ca : cb));
        mbar_wait(bar(B_EMPTY + stage), ((n - 3) >> 2) & 1, bud);
        if (!EXF) expect_w(bar(B_FULL + stage), STAGE_BYTES - (first ? ca : cb));
        tma_mc_w(sl + stage * STAGE_BYTES + rows * 128, first ? ma : mb, bar(B_FULL + stage),
                 (n & (KBLKS - 1)) * BK, (first ? toka : tokb) + rows);
        if (XPD && n >= XPS && n < KBLKS - XPD) {
          const uint8_t* a = xg + (((blockIdx.x & 127) * 16 + (lane >> 1)) * (K_ * 2) + (lane & 1) * 64 + (n + XPD) * 128);
          asm volatile("prefetch.global.L2 [%0];" ::"l"(a));
          if (!XPW) asm volatile("prefetch.global.L2 [%0+32];" ::"l"(a));
        }
        if (n <= KBLKS) {
          wait_until(t0, 32 * prmt((uint32_t)GATES, (uint32_t)(GATES >> 32), min(n, 7)));
          bulk_w(sl + ((n - 1) & 3) * STAGE_BYTES + X_BYTES, gp + (fta * KBLKS + n - 1) * SLAB_BYTES, SLAB_BYTES, bar(B_FULL + (n & 19)));
        }
        if (n == PN) wait_count(count + 32 * (1 + ((lds32(sl + OFF_EPOCH) & 256) ? 48 : 0) + 4 * ftb), bud);
        if (first) continue;
        if (n == KBLKS + 4 || n == KBLKS + 8) asm volatile("bar.sync %0, 64;" ::"r"(n & 8) : "memory");
        tma_w(sl + stage * STAGE_BYTES + TB * 128, &maps.m[M_W], bar(B_FULL + stage), (n - KBLKS) * BK, ftb * BF);
        tma_w(sl + stage * STAGE_BYTES + TB * 128 + 8192, &maps.m[M_W], bar(B_FULL + stage), (n - KBLKS) * BK, ftb * BF + 64);
      }
      const CUtensorMap *mx = &maps.m[M_XB], *mw = &maps.m[M_W];
      DBG(220);
      expect_w(bar(B_RDY), 16384);
      asm volatile("bar.sync 15, 96;" ::: "memory");
#pragma unroll
      for (int i = 0; i < 2; i++) {
        const uint32_t s = sl + i * STAGE_BYTES, w = sl + OFF_STG + 16384 + i * 32768, wb = bar(i ? B_FULL + 2 : B_RDY);
        if (i == 0) {
          tma_w(w, mw, wb, 12 * BK, ftb * BF + 64);
          tma_w(w + 8192, mw, wb, 13 * BK, ftb * BF + 64);
        }
        expect_w(bar(B_FULL + i), STAGE_BYTES);
        mbar_wait(bar(B_EMPTY + i), 0, bud);
        DBG(221 + i);
        tma_mc_w(s + rank * 12288, mx, bar(B_FULL + i), (12 + 2 * i + rank) * BK, tokb);
        tma_w(s + 24576, mw, bar(B_FULL + i), (12 + 2 * i) * BK, ftb * BF);
        tma_w(s + 32768, mw, bar(B_FULL + i), (13 + 2 * i) * BK, ftb * BF);
        if (i) {
          expect_w(wb, 16384);
          tma_w(w, mw, wb, (12 + 2 * i) * BK, ftb * BF + 64);
          tma_w(w + 8192, mw, wb, (13 + 2 * i) * BK, ftb * BF + 64);
        }
      }
      if (cb) mx++;
#pragma unroll
      for (int i = 2; i < 4; i++) {
        mbar_wait(bar(B_EMPTY + i), i & 1, bud);
        DBG(222 + i);
        if (i == 2) expect_w(bar(B_FULL + 3), 49152 - 4 * cb);
        tma_mc_w(sl + i * STAGE_BYTES + rank * 12288, mx, bar(B_FULL + 3), (8 + 2 * i + rank) * BK, tokb + TB / 2);
      }
      asm volatile(ELECT "@p red.relaxed.gpu.global.add.u32 [%0], %1;\n}\n" ::"l"(count), "r"(blockIdx.x < 2 * NUM_CTAS - 256 ? 1 : 2) : "memory");
    } else {
      const int p = warp - 1;
      uint32_t ep;
      asm volatile("ld.relaxed.gpu.global.u32 %0, [%1];" : "=r"(ep) : "l"(count) : "memory");
      cluster_arrive_relaxed();
      prefetch_map(&maps.m[p + (TR1 && p == 2 && (te & 15) >= 12 ? rank : 0)]);
      asm volatile("prefetch.global.L2 [%0];" ::"l"(xg + (((blockIdx.x * 16 + p * 8 + (lane >> 2)) & (M_ - 1)) * (K_ * 2) + (lane & 3) * 32)));
      const uint32_t so = OFF_STG + p * UNIT_BYTES;
      const uint32_t ua = sl + so + (lane & 3) * 256 + (((lane >> 2) ^ (2 * (lane & 3))) << 4);
      asm volatile("bar.sync 4, 128;" ::: "memory");
      if (!EPW && p == 2) {
        sts32(sl + OFF_EPOCH, ep);
        asm volatile("bar.arrive 1, 288;" ::: "memory");
      }
      int r = blockIdx.x, u = 128 + U0(r, p);
      const uint32_t job = maps.jobs[3 * r + p];
      uint32_t ph = 0, odd;
#pragma unroll 1
      do {
        wait_until(t0, D0 + (u - 128) * PU / 4);
        expect_w(bar(B_SLOT + p), UNIT_BYTES);
        tma_w(sl + so, &maps.m[M_Q], bar(B_SLOT + p), (u & 63) * 32, (u & ~63) + 32);
        DBG(16 + 8 * p + 2 * (r / NUM_CTAS));
        uint8_t* dst = gp + (((((u & 63) >> 2) * KBLKS + (u >> 6)) * 4 + (u & 3)) * 2048 + (lane >> 2) * 256 + (lane & 3) * 16);
        mbar_wait(bar(B_SLOT + p), ph, bud);
        asm volatile("and.b32 %0, %1, 256;" : "=r"(odd) : "r"(ep));
        DBG(184 + 4 * p + r / NUM_CTAS);
        uint32_t w[4][4];
#pragma unroll
        for (int b = 0; b < 4; b++) {
          uint32_t v[4][4];
          lds128(v[0], ua + b * 2048);
          lds128(v[1], (ua ^ 16) + b * 2048 + 128);
          lds128(v[2], ua + b * 2048 + 1024);
          lds128(v[3], (ua ^ 16) + b * 2048 + 1024 + 128);
#pragma unroll
          for (int j = 0; j < 4; j++) w[j][b] = make_word(v[0][j], v[1][j], v[2][j], v[3][j], word_key(odd));
        }
        st_words<0>(dst, w[0]); st_words<64>(dst, w[1]); st_words<128>(dst, w[2]); st_words<192>(dst, w[3]);
        __syncwarp();
        DBG(17 + 8 * p + 2 * (r / NUM_CTAS));
        ph ^= 1;
        r += NUM_CTAS;
        u = ph ? u + 3 * NUM_CTAS : job & 2047;
      } while (u < 1024);
      const int l = (job >> 11) & 511;
      const int ls = (l * 1366) >> 16, cg = l - 48 * ls;
      unsigned int* cnt = count + (32 + 6 * __shfl_sync(0xffffffffu, odd, 0));
      prefetch_map(&maps.m[M_XB + p]);
      prefetch_map(&maps.m[M_Q2]);
      if (l < 384) {
        uint32_t e[8];
        const __nv_bfloat16* s = lut + ((lane & 15) * N_ + 2048 + cg * 32 + (lane & 16));
        asm volatile("ld.global.nc.v4.u32 {%0, %1, %2, %3}, [%4];" : "=r"(e[0]), "=r"(e[1]), "=r"(e[2]), "=r"(e[3]) : "l"(s));
        asm volatile("ld.global.nc.v4.u32 {%0, %1, %2, %3}, [%4+16];" : "=r"(e[4]), "=r"(e[5]), "=r"(e[6]), "=r"(e[7]) : "l"(s));
        wait_until(t0, (job >> 20) * 8);
        expect_w(bar(B_SLOT + p), 2 * UNIT_BYTES);
        tma3_w(sl + so, &maps.m[M_Q2], bar(B_SLOT + p), 2048 + cg * 32, ls * 16, 0);
        tma3_w(sl + so + 32768, &maps.m[M_Q2], bar(B_SLOT + p), 2048 + cg * 32, ls * 16, 4);
        DBG(22 + 8 * p);
        uint32_t tab = sl + OFF_TAB + p * 1536 + (SHF ? lane * 32 : (lane >> 4) * 644);
        if (SHF) {
          sts128(tab, e);
          sts128(tab + 16, e + 4);
        } else {
#pragma unroll
          for (int i = 0; i < 8; i++) sts32(tab + (lane & 15) * 40 + 4 * i, e[i]);
          __syncwarp();
        }
        uint8_t* dst = gp + (W_OFF + cg * 65536 + ls * 256 + (lane >> 4) * 32768 + (lane & 15) * 16);
        const uint32_t src = sl + so + (lane & 15) * 128 + ((((lane >> 2) & 4) ^ (lane & 7)) << 4);
        mbar_wait(bar(B_SLOT + p), ph, bud);
#pragma unroll 1
        for (int c = 0; c < 64; c += 16, tab += 8, dst += 8192) {
          uint32_t v[8][4];
#pragma unroll
          for (int i = 0; i < 8; i++) lds128(v[i], (src ^ c) + (i & 3) * 2048 + (i >> 2) * 32768);
          if (SHF) {
            asm volatile("ld.shared.v2.u32 {%0, %1}, [%2];" : "=r"(e[0]), "=r"(e[1]) : "r"(tab) : "memory");
            convert_shfl<0>(v, e[0], dst);
            convert_shfl<1>(v, e[0], dst);
            convert_shfl<2>(v, e[1], dst);
            convert_shfl<3>(v, e[1], dst);
          } else {
          convert_col<0>(v, tab, dst);
          convert_col<1>(v, tab, dst);
          convert_col<2>(v, tab, dst);
          convert_col<3>(v, tab, dst);
          }
        }
        __syncwarp();
        DBG(23 + 8 * p);
      }
      arrive_w(bar(B_LAST));
      if (l < 384)
        asm volatile(ELECT "@p fence.proxy.async.global;\n@p red.release.gpu.global.add.u32 [%0], %1;\n}\n"
                     ::"l"(cnt + 32 * ((cg & ~3) + min(ls >> 1, 2))), "r"(ls < 4 ? 8 : 4) : "memory");
      cluster_wait();
      TILES();
      prefetch_map(&maps.m[p ? M_O32 : M_W]);
      if (p > 0) {
        asm volatile("bar.sync %0, 160;" ::"r"(12 + p) : "memory");
        if (FEN) asm volatile("fence.proxy.async.shared::cta;" ::: "memory");
        uint32_t t1 = clock();
#pragma unroll 1
        for (int i = 0; i < TA; i += OB, t1 += PC * OB / 32) {
          wait_until(t1, 0);
          const int rr = min(i ^ 128, (big ? TA : TC) - OB);
          if (i == 128) {
            bulk_wait_read();
            asm volatile("bar.arrive 15, 96;" ::: "memory");
          }
          store_w(&maps.m[M_O32], sl + OFF_STG + (p - 1) * 32768 + rr * 128, fta * BF + 64 * (p - 1), toka + rr);
        }
        bulk_wait_read();
        DBG(227 + p);
        asm volatile("bar.arrive %0, 160;" ::"r"(12 + p) : "memory");
      } else {
        if (blockIdx.x < 48) count[32 * (50 + blockIdx.x) - (cnt - count)] = 0;
#pragma unroll 1
        for (int i = 1; i < 3; i++) {
          wait_count(cnt + 32 * (4 * ftb + i), bud);
          asm volatile("bar.arrive %0, 64;" ::"r"(8 * i - 8) : "memory");
        }
      }
    }
    asm volatile("exit;");
  }
  const int cw = wg - 1;
  TILES();
  cluster_arrive_relaxed();
  if (warp >= 2) {
    ld_lut<0>(cf, lut + (fta * BF + 4 * (lane & 3) * N_ + 64 * cw + 32 * (warp & 1) + (lane & 16) + ((lane >> 1) & 6)));
  } else if (cw) {
    spin_until(t0, S1D);
    ld_codes(cf, src);
  } else if (EPW) {
    sts32(sl + OFF_EPOCH, ep0);
    asm volatile("bar.arrive 1, 256;" ::: "memory");
  }
  if (EPW) {
    if (w12 >= 6) asm volatile("bar.sync 1, 256;" ::: "memory");
  } else asm volatile("bar.sync 1, 288;" ::: "memory");
  const uint32_t odd = lds32(sl + OFF_EPOCH) & 256;
  DBG(40 + w12);
  if (warp >= 2) store_planes(sl + OFF_PL + cw * 32768 + (warp & 1) * 1024 + (lane & 28) * 32 + (lane & 3) * 16, cf);
  else {
    uint8_t* dst = gp + (((blockIdx.x & 120) * 2 + cw) * SLAB_BYTES + (blockIdx.x & 7) * 1024 + (tid & 63) * 16);
    const uint32_t tb = sl + OFF_STG + 61440 + cw * 1024;
#pragma unroll
    for (int j = 0; j < 4; j++)
      sts32(tb + (lane & 3) * 256 + j * 64 + (lane & 12) * 4 + ((tid >> 2) & 12), make_word(cf[j], cf[4 + j], cf[8 + j], cf[12 + j], word_key(odd)));
    asm volatile("bar.sync %0, 64;" ::"r"(6 + cw) : "memory");
    lds128(cf, tb + (tid & 63) * 16);
    st_words<0>(dst, cf);
  }
  DBG(52 + w12);
  asm volatile("setmaxnreg.inc.sync.aligned.u32 216;");
  uint32_t rel = (tid & 127) < 2 ? mapa(bar(B_EMPTY), lane) : 0u;
  uint32_t tg = (w12 - 4) * 1024 + lane * 16;
  uint32_t tw = sl + X_BYTES + tg;
  const uint8_t* gt = gp + (tg + fta * KBLKS * SLAB_BYTES);
  uint32_t tag = (1u << 28) - (odd << 19), sc = 0x3c00 + 8 * odd;
  asm volatile("" : "+r"(tw), "+l"(gt), "+r"(rel), "+r"(tag), "+r"(sc));
  Planes pl;
  uint32_t A[16], P[8];
  float acc[TA / 2];
  DBG(64 + cw);
  if (PLF) {
  asm volatile("bar.sync %0, 128;" ::"r"(2 + cw) : "memory");
#pragma unroll
  for (int k = 0; k < 4; k++) lds128(pl.v[k], sl + OFF_PL + cw * 32768 + (tid & 124) * 16 + 16 * k);
  }
  {
    const uint32_t td = sl + 3 * STAGE_BYTES - 8192 + (w12 >> 1) * 4096 + (lane & 3) * 256 + ((((tid >> 3) & 4) ^ (lane >> 4) ^ (2 * (lane & 3))) << 4) + (lane & 12);
    mbar_wait(bar(B_DIR), 0, bud);
    DBG(88 + cw);
#pragma unroll
    for (int k = 0; k < 4; k++) {
      const uint32_t a = (td ^ ((k & 2) << 4)) + (k & 1) * 2048;
      P[2 + (k & 1) + 2 * (k & 2)] = make_word(lds32(a), lds32((a ^ 16) + 128), lds32(a + 1024), lds32((a ^ 16) + 1152), word_key(odd));
    }
  }
  if (!PLF) {
  asm volatile("bar.sync %0, 128;" ::"r"(2 + cw) : "memory");
#pragma unroll
  for (int k = 0; k < 4; k++) lds128(pl.v[k], sl + OFF_PL + cw * 32768 + (tid & 124) * 16 + 16 * k);
  }
  mbar_wait(bar(B_FULL), 0, bud);
  DBG(66 + cw);
  auto tile1 = [&](auto nh) {
    uint32_t d = UD, dn, fb = bar(B_FULL + 1), pa = 0;
#pragma unroll 1
    for (int n = 0; n < KBLKS; n++) {
      bool ok;
#pragma unroll
      for (int b = 0; b < 4; b++) {
        const int m = n + 1;
        if (b == WB && !EP1) mbar_wait_fast(fb, (m >> 2) & 1, bud);
        if (b == WB && EP1 == 1 && !ok) mbar_wait(fb, (m >> 2) & 1, bud);
        if (b == 1 && EP1 == 3) ok = mbar_test(fb, (m >> 2) & 1);
        if (b == 1 && EP1 == 5) ok = mbar_peek(fb, (m >> 2) & 1);
        if (b == 2 && EP1 >= 4 && __builtin_expect(!ok, 0)) {
          mbar_wait(fb, (m >> 2) & 1, bud);
          lds128(P, tw + pa);
          lds128(P + 4, tw + pa + 512);
        }
        if (b == 2) {
#pragma unroll 1
          while (__builtin_expect(!words_ok(P, tag), 0)) {
            if ((bud += 16) >= 0x100000) break;
            asm volatile("{\n.reg .u64 a;\nmad.wide.u32 a, %8, 8192, %9;\nld.relaxed.gpu.global.v4.u32 {%0, %1, %2, %3}, [a];\n"
                         "ld.relaxed.gpu.global.v4.u32 {%4, %5, %6, %7}, [a+512];\n}\n"
                         : "=r"(P[0]), "=r"(P[1]), "=r"(P[2]), "=r"(P[3]), "=r"(P[4]), "=r"(P[5]), "=r"(P[6]), "=r"(P[7]) : "r"(n), "l"(gt) : "memory");
          }
          __syncwarp();
        }
        lookup4(pl, 0, P[b ^ 2], sc, A[4 * b], A[4 * b + 2]);
        lookup4(pl, 1, P[4 + (b ^ 2)], sc, A[4 * b + 1], A[4 * b + 3]);
        if (b == 1) {
          if ((EP1 == 2 || EP1 == 3) && !ok) mbar_wait(fb, (m >> 2) & 1, bud);
          lds128(P, tw + pa);
          lds128(P + 4, tw + pa + 512);
        }
        if (b == 3) {
          asm volatile("mad.lo.u32 %0, %1, %3, %2;" : "=r"(dn) : "r"(m & 3), "r"(UD), "n"(STAGE_BYTES / 16));
          asm volatile("mad.lo.u32 %0, %1, 8, %2;" : "=r"(fb) : "r"((m + 1) & 19), "r"(bar(B_FULL)));
          asm volatile("mul.lo.u32 %0, %1, %2;" : "=r"(pa) : "r"(m & 3), "n"(STAGE_BYTES));
        }
        if (((WD >> (4 * b)) & 3) == 1) wgmma_wait<1>();
        if (((WD >> (4 * b)) & 3) == 2) wgmma_wait<2>();
        if (b == RB) mbar_arrive_remote_if(rel + 8 * ((n - 1) & 3), rel);
        if (b == S1B && n == S1N && cw == 1) asm volatile("bar.sync 9, 256;" ::: "memory");
        if (b == 0 && (EP1 == 1 || EP1 == 2)) ok = mbar_test(fb, (m >> 2) & 1);
        if (b == 0 && EP1 == 4) ok = mbar_peek(fb, (m >> 2) & 1);
        wgmma_fence();
        if constexpr (ONE) wgmma_rs<decltype(nh)::v + TB>(acc, A + 4 * b, d + 2 * b, b > 0 || n != 0);
        else {
          wgmma_rs<decltype(nh)::v>(acc + TB / 2, A + 4 * b, d + 2 * b + TB * 8, b > 0 || n != 0);
          wgmma_rs<TB>(acc, A + 4 * b, d + 2 * b, b > 0 || n != 0);
        }
        wgmma_commit();
      }
      d = dn;
    }
  };
  if (big) tile1(IC<TA - TB>()); else tile1(IC<TC - TB>());
  if (cw != 1) asm volatile("bar.arrive 9, 256;" ::: "memory");
  const uint32_t stg = sl + OFF_STG + cw * 32768;
  const uint32_t so8 = stg + ((lane & 7) + ((lane >> 4) << 3)) * 128 + (((2 * warp + ((lane >> 3) & 1)) ^ (lane & 7)) << 4);
  DBG(212 + cw);
  mbar_wait(bar(B_FULL), 0, bud);
  DBG(214 + cw);
  if (NP > 1 && !W17) mbar_wait(bar(B_FULL + 1), 0, bud);
  DBG(216 + cw);
  const uint64_t ub = maps.desc, ua = ub + (TB * 8 + cw * 512);
  wgmma_wait<0>();
  mbar_arrive_remote_if(rel + 24, rel);
  fence_regs(acc);
  DBGR(0, 68 + cw);
  {
    uint32_t o[64];
#pragma unroll
    for (int k = 0; k < 48; k++) o[k] = pack_bf16(acc[2 * k], acc[2 * k + 1]);
#pragma unroll
    for (int k = 0; k < 48; k++) asm volatile("" : "+r"(o[k]) :: "memory");
    DBG(92 + cw);
    wgmma_fence();
#pragma unroll
    for (int b = 0; b < 4 * NP; b++) {
      const int so = (b >> 2) * (STAGE_BYTES / 16) + 2 * (b & 3);
      if (b == 4 && W17) mbar_wait(bar(B_FULL + 1), 0, bud);
      wgmma_ss<TB>(acc, ua + so, ub + so, b != 0);
      if ((b & 3) == 3 || b == 4) wgmma_commit();
      if (b == 0) {
#pragma unroll
        for (int k = 48; k < 64; k++) o[k] = pack_bf16(acc[2 * k], acc[2 * k + 1]);
      }
      if (b == 4) {
        wgmma_wait<1>();
        mbar_arrive_remote_if(rel, rel);
      }
#pragma unroll
      for (int j = 0; j < 16; j++)
        if (j * NSB / 16 + SB0 == b) stmatrix_x4_t(so8 + j * 2048, o[4 * j], o[4 * j + 1], o[4 * j + 2], o[4 * j + 3]);
    }
  }
  if (!FEN) asm volatile("fence.proxy.async.shared::cta;" ::: "memory");
  asm volatile("bar.arrive %0, 160;" ::"r"(13 + cw) : "memory");
  cluster_wait();
  DBG(70 + cw);
  auto tile2 = [&](auto nt) {
#pragma unroll 1
    for (int n = NP; n < KBLKS - 4; n++) {
      const uint32_t so = (n & 3) * (STAGE_BYTES / 16);
      mbar_wait_fast(bar(B_FULL) + 8 * (n & 3), (n >> 2) & 1, bud);
      wgmma_fence();
      wgmma_ss<decltype(nt)::v>(acc, ua + so, ub + so, 1);
      wgmma_commit();
      wgmma_wait<1>();
      mbar_arrive_remote_if(rel + 8 * ((n - 1) & 3), rel);
#pragma unroll
      for (int b = 1; b < 4; b++) wgmma_ss<decltype(nt)::v>(acc, ua + so + 2 * b, ub + so + 2 * b, 1);
      wgmma_commit();
    }
  };
  if (big) tile2(IC<TD>()); else tile2(IC<TB>());
  uint32_t W[64];
  float c2[TB / 2];
  DBGR(1, 72 + cw);
  const uint32_t wa = sl + (warp * 16 + (lane & 15)) * 128 + (((lane >> 4) ^ (lane & 7)) << 4);
  const uint32_t w0 = wa + (cw ? OFF_STG + 16384 : 24576), w2 = wa + (cw ? OFF_STG + 49152 : STAGE_BYTES + 24576);
  auto ldw = [&](int b) { ldmatrix_x4(W + 4 * b, ((b & 8 ? w2 : w0) ^ ((b & 3) << 5)) + ((b >> 2) & 1) * 8192); };
  const uint32_t b2 = bar(B_FULL + 1 + cw);
  mbar_wait(bar(cw ? B_RDY : B_FULL), 1, bud);
  if (cw) DBG(226);
#pragma unroll
  for (int b = 0; b < PF; b++) ldw(b);
  bool ok = mbar_peek(b2, 1);
  wgmma_wait<0>();
  mbar_arrive_remote_if(rel + 24, rel);
  if (cw) {
    mbar_wait(b2, 1, bud);
    ok = true;
    DBG(227);
  }
#pragma unroll
  for (int k = 0; k < TB / 2; k++) asm volatile("mov.b32 %0, %1;" : "=f"(c2[k]) : "f"(acc[k]) : "memory");
#pragma unroll
  for (int h = 0; h < 2; h++) {
    if (h) mbar_wait(bar(B_FULL + 3), 1, bud);
    if (h || cw) asm volatile("bar.sync %0, 256;" ::"r"(9 + 2 * h + cw) : "memory");
    DBGR(2 + 3 * h, 74 + 6 * h + cw);
    auto half = [&](auto nn) {
#pragma unroll
      for (int i = 0; i < 16; i++) {
        if (i >= QD && i <= QN) wgmma_wait<QD - 1>();
        if (i == 0 || (h == 0 && ((FM >> i) & 1))) wgmma_fence();
        const int off = ((2 * h + (i >> 3)) * STAGE_BYTES + ((i >> 2) & 1) * 12288) / 16 + 2 * (i & 3);
        if constexpr (decltype(nn)::v == 96) wgmma_rl<96>(c2 + 48 * h, W + 4 * i, ub + off);
        else wgmma_rs<decltype(nn)::v>(c2 + 48 * h, W + 4 * i, UD + off, 1);
        if (i == NSI - 1 || i < QN) wgmma_commit();
        if (h == 0) {
#pragma unroll
          for (int e = 0; e < LPS; e++) {
            const int j = (i - LD0) * LPS + PF + e;
            if (j == 8 && !ok) mbar_wait(b2, 1, bud);
            if (j >= PF && j < 16) ldw(j);
          }
        }
      }
      wgmma_commit();
    };
    if (N88 && h && big) half(IC<TD - TB / 2>()); else half(IC<TB / 2>());
    wgmma_wait<1>();
    if (!h || !cw) asm volatile("bar.arrive %0, 256;" ::"r"(10 + 2 * h + cw) : "memory");
    const int r2 = h ? (big ? TD - 96 : TB - 96) : 0;
    if (!h) asm volatile("bar.sync %0, 160;" ::"r"(13 + cw) : "memory");
    wgmma_wait<0>();
#pragma unroll
    for (int k = 0; k < 48; k++) asm volatile("" : "+f"(c2[48 * h + k]) :: "memory");
    DBGR(3 + 3 * h, 76 + 6 * h + cw);
    stage_part<6>(c2 + 48 * h, so8 + 96 * 128 * h);
    asm volatile("fence.proxy.async.shared::cta;" ::: "memory");
    asm volatile("bar.sync %0, 128;" ::"r"(2 + cw) : "memory");
    if (O24) store_w(&maps.m[M_O96], stg + (r2 + 24 * warp) * 128, 2048 + ftb * BF + 64 * cw, tokb + r2 + 24 * warp);
    else if (warp == 0) store_w(&maps.m[M_O96], stg + r2 * 128, 2048 + ftb * BF + 64 * cw, tokb + r2);
    DBGR(4 + 3 * h, 78 + 6 * h + cw);
  }
  bulk_wait_read();
}

typedef CUresult (*EncodeFn)(CUtensorMap*, CUtensorMapDataType, cuuint32_t, void*, const cuuint64_t*, const cuuint64_t*,
                             const cuuint32_t*, const cuuint32_t*, CUtensorMapInterleave, CUtensorMapSwizzle,
                             CUtensorMapL2promotion, CUtensorMapFloatOOBfill);

}

extern "C" void kernel_launch(void* const* d_in, const int* in_sizes, int n_in, void* d_out, int out_size) {
  const __nv_bfloat16* x = (const __nv_bfloat16*)d_in[0];
  const int* qw = (const int*)d_in[1];
  const __nv_bfloat16* lut = (const __nv_bfloat16*)d_in[2];

  static EncodeFn enc = nullptr;
  static unsigned int* count = nullptr;
  static uint8_t* gp = nullptr;
  if (!enc) {
    cudaDriverEntryPointQueryResult q;
    void* fn = nullptr;
    cudaGetDriverEntryPoint("cuTensorMapEncodeTiled", &fn, cudaEnableDefault, &q);
    enc = (EncodeFn)fn;
    cudaGetSymbolAddress((void**)&count, g_count);
    cudaGetSymbolAddress((void**)&gp, g_p);
    cudaFuncSetAttribute(fused_kernel, cudaFuncAttributeMaxDynamicSharedMemorySize, SMEM_BYTES);
  }
  Maps maps;
  const cuuint32_t es[3] = {1, 1, 1};
  auto map2 = [&](int i, CUtensorMapDataType t, const void* p, int d0, int d1, int bytes, int b0, int b1, CUtensorMapL2promotion pr) {
    cuuint64_t dims[2] = {(cuuint64_t)d0, (cuuint64_t)d1};
    cuuint64_t strides[1] = {(cuuint64_t)d0 * bytes};
    cuuint32_t box[2] = {(cuuint32_t)b0, (cuuint32_t)b1};
    enc(&maps.m[i], t, 2, (void*)p, dims, strides, box, es, CU_TENSOR_MAP_INTERLEAVE_NONE, CU_TENSOR_MAP_SWIZZLE_128B, pr, CU_TENSOR_MAP_FLOAT_OOB_FILL_NONE);
  };
  map2(M_XA, CU_TENSOR_MAP_DATA_TYPE_BFLOAT16, x, K_, M_, 2, BK, TA / 2, XPROM);
  map2(M_XC, CU_TENSOR_MAP_DATA_TYPE_BFLOAT16, x, K_, M_, 2, BK, TC - TA / 2, XPROM);
  map2(M_XD, CU_TENSOR_MAP_DATA_TYPE_BFLOAT16, x, K_, M_, 2, BK, TD - TB / 2, XPROM);
  map2(M_XB, CU_TENSOR_MAP_DATA_TYPE_BFLOAT16, x, K_, M_, 2, BK, TB / 2, XPROM);
  map2(M_O96, CU_TENSOR_MAP_DATA_TYPE_BFLOAT16, d_out, N_, M_, 2, 64, O24 ? 24 : 96, CU_TENSOR_MAP_L2_PROMOTION_NONE);
  map2(M_O32, CU_TENSOR_MAP_DATA_TYPE_BFLOAT16, d_out, N_, M_, 2, 64, OB, CU_TENSOR_MAP_L2_PROMOTION_NONE);
  map2(M_Q, CU_TENSOR_MAP_DATA_TYPE_INT32, qw, N_, K_, 4, 32, BK, QPROM);
  map2(M_W, CU_TENSOR_MAP_DATA_TYPE_BFLOAT16, gp + W_OFF, K_, N_ - 2048, 2, BK, 64, XPROM);
  {
    cuuint64_t dims[3] = {(cuuint64_t)N_, (cuuint64_t)K_ / 8, 8};
    cuuint64_t strides[2] = {(cuuint64_t)N_ * 32, (cuuint64_t)N_ * 4};
    cuuint32_t box[3] = {32, 16, 4};
    enc(&maps.m[M_Q2], CU_TENSOR_MAP_DATA_TYPE_INT32, 3, (void*)qw, dims, strides, box, es, CU_TENSOR_MAP_INTERLEAVE_NONE,
        CU_TENSOR_MAP_SWIZZLE_128B, QPROM, CU_TENSOR_MAP_FLOAT_OOB_FILL_NONE);
  }
  {
    cuuint64_t dims[3] = {32, (cuuint64_t)K_, (cuuint64_t)N_ / 32};
    cuuint64_t strides[2] = {(cuuint64_t)N_ * 4, 128};
    cuuint32_t box[3] = {32, 32, 4};
    enc(&maps.m[M_D], CU_TENSOR_MAP_DATA_TYPE_INT32, 3, (void*)qw, dims, strides, box, es, CU_TENSOR_MAP_INTERLEAVE_NONE,
        CU_TENSOR_MAP_SWIZZLE_128B, QPROM, CU_TENSOR_MAP_FLOAT_OOB_FILL_NONE);
  }
  maps.desc = (0x40000040ull << 32) + UD;
  for (int t = 0; t < 66; t++) {
    const int u = t - 32, g = t < 32 ? t & 7 : 1 + u % 7, j = t < 32 ? t >> 3 : 4 + u / 7;
    int cl = t >= 60 ? (int)((0x413B3F394035ull >> (8 * (t - 60))) & 0xff) : g == 7 ? 48 + 2 * j : g ? 6 * j + g - 1 : std::min(49 + 6 * j, 87 - 12 * j);
    if (GMAP == 0) cl = (t + 4) % 66;
    const int yi = cl / 6, fb = 2 * (cl % 6);
    const int fa = cl < 48 ? fb : 12 + 2 * (cl & 1), ta = cl < 48 ? TA * yi : std::min(TC * ((cl - 48) >> 1), M_ - TC);
    maps.tiles[t >= 62 ? t & 3 : t + 4] = fa | fb << 4 | ta << 5 | (TD * yi + (TB - TD) * std::max(yi - 8, 0)) << 13;
  }
  {
    int third[396], t2[396], nt = 0, na = 0;
    for (int i = 0; i < 396; i++) {
      const bool isb = (maps.tiles[i / 6] & 15) >= 12;
      third[i] = isb && i % 3 < NB3;
      t2[i] = 1;
      nt += third[i];
    }
    const int need = 104 - nt;
    for (int b = 0, k = 0; b < 132; b++) {
      if ((maps.tiles[b / 2] & 15) >= 12) continue;
      if ((na / 2 + 1) * need / 96 != (na / 2) * need / 96 || need >= 96) {
        third[3 * b] = 1;
        if (T2L == 0 && k >= need - 12) t2[3 * b] = 0;
        if (T2L == 1 && k < 12) t2[3 * b] = 0;
        k++;
      }
      na++;
    }
    if (NB3 == 0) for (int b = 131, k = 0; k < 8; b--) if ((maps.tiles[b / 2] & 15) >= 12) { third[3 * b] = 1; t2[3 * b] = 0; k++; }
    int u = 920, l = 0;
    for (int i = 0; i < 396; i++) maps.jobs[i] = third[i] ? u++ : 1024;
    std::pair<int, int> rd[396];
    for (int i = 0; i < 396; i++) rd[i] = {third[i] ? (int)maps.jobs[i] - 128 : 396 + U0(i / 3, i % 3), i};
    std::sort(rd, rd + 396);
    for (int k = 0; k < 396; k++) {
      const int i = rd[k].second;
      if (t2[i]) maps.jobs[i] |= l << 11 | std::min(LCAP, LT0 + l * LTS) / 8 << 20, l++;
      else maps.jobs[i] |= 384 << 11;
    }
  }
  fused_kernel<<<NUM_CTAS, NTHREADS, SMEM_BYTES, cudaStreamPerThread>>>(count, lut, gp, qw, (const uint8_t*)x, maps);
}
```

```cpp
#include <cuda_runtime.h>
#include <cuda_bf16.h>
#include <cuda.h>
#include <stdint.h>
#include <cstdio>
#include <algorithm>

namespace {

constexpr int M_ = 2048, K_ = 1024, N_ = 3584;
constexpr int BF = 128, BK = 64;
constexpr int TA = 256, TB = 192;
#define TCC 232
constexpr int TC = TCC, TD = 184;
constexpr int STAGES = 4;
constexpr int KBLKS = K_ / BK;
constexpr int X_BYTES = TA * BK * 2;
constexpr int UNIT_BYTES = BK * 32 * 4;
constexpr int SLAB_BYTES = BF * BK;
constexpr int STAGE_BYTES = X_BYTES + SLAB_BYTES;
constexpr int OFF_STG = STAGES * STAGE_BYTES;
constexpr int OFF_PL = OFF_STG + 3 * UNIT_BYTES;
constexpr int OFF_TAB = OFF_PL + 2048;
constexpr int OFF_BAR = OFF_STG + 65536;
constexpr int W_OFF = 16 * KBLKS * SLAB_BYTES;
constexpr int SMEM_BYTES = OFF_BAR + 512;
constexpr int NUM_CTAS = 132;
constexpr int NTHREADS = 384;
constexpr int NPACK = 3;
#define XT0 1400
#define WT0 2350
#define WTS 1000
#define S1D 400
#define PC 900
#define OB 32
#define WD 0x2212
#define RB 1
#define D0 600
#define WB 1
#define LT0 7800
#define LTS 13
#define XPROM CU_TENSOR_MAP_L2_PROMOTION_L2_128B
#define QPROM CU_TENSOR_MAP_L2_PROMOTION_L2_128B
#define S1B 1
#define S1N 15
#define NP 2
#define PN 16
#define EP1 1
#define W17 1
#define SB0 0
#define NSB 8
#define FEN 1
#define GMAP 1
#define EPW 1
#define LCAP 14000
#define NB3 1
#define ORD 1
#define PU 36
#define U0(r, p) (ORD == 0 ? 3 * (r) + (p) : ORD == 1 ? 132 * (p) + (r) : (p) ? 131 + 2 * (r) + (p) : (r))
#define G0 WT0
#define G1 (WT0 + WTS)
#define G2 (WT0 + 2 * WTS)
#define G3 (WT0 + 3 * WTS)
#define G4 (WT0 + 4 * WTS)
#define G5 (WT0 + 5 * WTS)
constexpr uint64_t GATES = (uint64_t)(G0 / 32) << 8 | (uint64_t)(G1 / 32) << 16 | (uint64_t)(G2 / 32) << 24 | (uint64_t)(G3 / 32) << 32 | (uint64_t)(G4 / 32) << 40 | (uint64_t)(G5 / 32) << 48;
#define TR1 1
#define TR2 1
#define SW 0
#define XPD 2
#define XPS 2
#define XPW 1
#define SHF 1
#define PLF 1
#define EXF 1
#define PF 8
#define LD0 1
#define LPS 2
#define QD1 5
#define QN1 12
#define K0 4
#define QD0 3
#define QN0 8
#define FM0 0x113c
#define K00 4
#define TCH 0
#define IX 8
#define UH 2
#define NA 13
#define UA 12
#define NSH 2
static_assert(SMEM_BYTES <= 232448, "smem");
static_assert(TB * 128 + 2 * SLAB_BYTES == STAGE_BYTES, "stage");
constexpr int B_FULL = 0, B_EMPTY = 4, B_DIR = 8, B_SLOT = 9, NBARS = 12, B_LAST = 16, B_RDY = B_DIR;
constexpr int OFF_EPOCH = OFF_BAR + 8 * NBARS;
constexpr uint32_t SB = 1024;
constexpr uint32_t UD = (SB >> 4) | (1u << 16);
enum { M_Q, M_D, M_XA, M_XC, M_XB, M_XD, M_O24, M_O32, M_W, M_Q2, NMAPS };

__device__ __align__(1024) uint8_t g_p[W_OFF + 12 * KBLKS * 2 * SLAB_BYTES];
__device__ __align__(128) unsigned int g_count[32 * 97];

__device__ __forceinline__ uint32_t smem_u32(const void* p) { return (uint32_t)__cvta_generic_to_shared(p); }
__device__ __forceinline__ void mbar_init(uint32_t bar, uint32_t cnt) {
  asm volatile("mbarrier.init.shared::cta.b64 [%0], %1;" ::"r"(bar), "r"(cnt) : "memory");
}
__device__ __forceinline__ void mbar_wait(uint32_t bar, uint32_t parity, uint32_t& c) {
  asm volatile(
      "{\n.reg .pred p;\n"
      "SPIN:\n"
      "mbarrier.try_wait.parity.shared::cta.b64 p, [%1], %2;\n"
      "add.u32 %0, %0, 1;\n"
      "setp.ge.or.u32 p, %0, 0x100000, p;\n"
      "@!p bra.uni SPIN;\n}\n"
      : "+r"(c) : "r"(bar), "r"(parity) : "memory");
}
__device__ __forceinline__ void mbar_wait_fast(uint32_t bar, uint32_t parity, uint32_t& c) {
  asm volatile(
      "{\n.reg .pred p;\n"
      "SPIN:\n"
      "mbarrier.try_wait.parity.shared::cta.b64 p, [%1], %2;\n"
      "@p bra.uni DONE;\n"
      "add.u32 %0, %0, 1;\n"
      "setp.lt.u32 p, %0, 0x100000;\n"
      "@p bra.uni SPIN;\n"
      "DONE:\n}\n"
      : "+r"(c) : "r"(bar), "r"(parity) : "memory");
}
__device__ __forceinline__ bool mbar_test(uint32_t bar, uint32_t parity) {
  uint32_t ok;
  asm volatile("{\n.reg .pred p;\nmbarrier.try_wait.parity.shared::cta.b64 p, [%1], %2;\nselp.u32 %0, 1, 0, p;\n}\n" : "=r"(ok) : "r"(bar), "r"(parity) : "memory");
  return ok != 0;
}
__device__ __forceinline__ bool mbar_peek(uint32_t bar, uint32_t parity) {
  uint32_t ok;
  asm volatile("{\n.reg .pred p;\nmbarrier.test_wait.parity.shared::cta.b64 p, [%1], %2;\nselp.u32 %0, 1, 0, p;\n}\n" : "=r"(ok) : "r"(bar), "r"(parity) : "memory");
  return ok != 0;
}
__device__ __forceinline__ void mbar_arrive(uint32_t bar) {
  asm volatile("mbarrier.arrive.shared::cta.b64 _, [%0];" ::"r"(bar) : "memory");
}
__device__ __forceinline__ uint32_t mapa(uint32_t a, uint32_t cta) {
  uint32_t r;
  asm("mapa.shared::cluster.u32 %0, %1, %2;" : "=r"(r) : "r"(a), "r"(cta));
  return r;
}
__device__ __forceinline__ void mbar_arrive_remote_if(uint32_t ra, uint32_t cond) {
  asm volatile("{\n.reg .pred p;\nsetp.ne.u32 p, %1, 0;\n@p mbarrier.arrive.shared::cluster.b64 _, [%0];\n}\n" ::"r"(ra), "r"(cond) : "memory");
}
#define ELECT "{\n.reg .pred p;\nelect.sync _|p, 0xffffffff;\n"
__device__ __forceinline__ void expect_w(uint32_t bar, uint32_t bytes) {
  asm volatile(ELECT "@p mbarrier.arrive.expect_tx.shared::cta.b64 _, [%0], %1;\n}\n" ::"r"(bar), "r"(bytes) : "memory");
}
__device__ __forceinline__ void arrive_w(uint32_t bar) {
  asm volatile(ELECT "@p mbarrier.arrive.shared::cta.b64 _, [%0];\n}\n" ::"r"(bar) : "memory");
}
__device__ __forceinline__ void tma_mc_w(uint32_t dst, const CUtensorMap* map, uint32_t bar, int c0, int c1) {
  asm volatile(
      ELECT "@p cp.async.bulk.tensor.2d.shared::cluster.global.mbarrier::complete_tx::bytes.multicast::cluster [%0], [%1, {%3, %4}], [%2], %5;\n}\n"
      ::"r"(dst), "l"((uint64_t)map), "r"(bar), "r"(c0), "r"(c1), "h"((uint16_t)3) : "memory");
}
__device__ __forceinline__ void bulk_w(uint32_t dst, const void* src, uint32_t bytes, uint32_t bar) {
  asm volatile(ELECT "@p cp.async.bulk.shared::cluster.global.mbarrier::complete_tx::bytes [%0], [%1], %2, [%3];\n}\n"
               ::"r"(dst), "l"(src), "r"(bytes), "r"(bar) : "memory");
}
__device__ __forceinline__ void tma_w(uint32_t dst, const CUtensorMap* map, uint32_t bar, int c0, int c1) {
  asm volatile(
      ELECT "@p cp.async.bulk.tensor.2d.shared::cluster.global.mbarrier::complete_tx::bytes [%0], [%1, {%3, %4}], [%2];\n}\n"
      ::"r"(dst), "l"((uint64_t)map), "r"(bar), "r"(c0), "r"(c1) : "memory");
}
__device__ __forceinline__ void tma3_w(uint32_t dst, const CUtensorMap* map, uint32_t bar, int c0, int c1, int c2) {
  asm volatile(
      ELECT "@p cp.async.bulk.tensor.3d.shared::cluster.global.mbarrier::complete_tx::bytes [%0], [%1, {%3, %4, %5}], [%2];\n}\n"
      ::"r"(dst), "l"((uint64_t)map), "r"(bar), "r"(c0), "r"(c1), "r"(c2) : "memory");
}
__device__ __forceinline__ void store_w(const CUtensorMap* map, uint32_t src, int c0, int c1) {
  asm volatile(ELECT "@p cp.async.bulk.tensor.2d.global.shared::cta.bulk_group [%0, {%2, %3}], [%1];\n}\n"
               "cp.async.bulk.commit_group;"
               ::"l"((uint64_t)map), "r"(src), "r"(c0), "r"(c1) : "memory");
}
__device__ __forceinline__ void bulk_wait_read() { asm volatile("cp.async.bulk.wait_group.read 0;" ::: "memory"); }
__device__ __forceinline__ void cluster_arrive_relaxed() { asm volatile("barrier.cluster.arrive.relaxed.aligned;" ::: "memory"); }
__device__ __forceinline__ void cluster_wait() { asm volatile("barrier.cluster.wait.acquire.aligned;" ::: "memory"); }
__device__ __forceinline__ void wgmma_fence() { asm volatile("wgmma.fence.sync.aligned;" ::: "memory"); }
__device__ __forceinline__ void wgmma_commit() { asm volatile("wgmma.commit_group.sync.aligned;" ::: "memory"); }
template <int N> __device__ __forceinline__ void wgmma_wait() { asm volatile("wgmma.wait_group.sync.aligned %0;" ::"n"(N) : "memory"); }
template <int N> __device__ __forceinline__ void fence_regs(float (&p)[N]) {
#pragma unroll
  for (int i = 0; i < N; i++) asm volatile("" : "+f"(p[i]) :: "memory");
}

template <int N> __device__ __forceinline__ void wgmma_rs(float* d, const uint32_t* a, uint32_t descB, uint32_t accum);
template <> __device__ __forceinline__ void wgmma_rs<256>(float* d, const uint32_t* a, uint32_t descB, uint32_t accum) {
  asm volatile(
    "{\n.reg .pred p;\n.reg .b64 db;\n"
    "setp.ne.b32 p, %133, 0;\n"
    "mov.b64 db, {%132, 0x40000040};\n"
    "wgmma.mma_async.sync.aligned.m64n256k16.f32.bf16.bf16 "
    "{%0, %1, %2, %3, %4, %5, %6, %7, %8, %9, %10, %11, %12, %13, %14, %15, %16, %17, %18, %19, %20, %21, %22, %23, %24, %25, %26, %27, %28, %29, %30, %31, %32, %33, %34, %35, %36, %37, %38, %39, %40, %41, %42, %43, %44, %45, %46, %47, %48, %49, %50, %51, %52, %53, %54, %55, %56, %57, %58, %59, %60, %61, %62, %63, %64, %65, %66, %67, %68, %69, %70, %71, %72, %73, %74, %75, %76, %77, %78, %79, %80, %81, %82, %83, %84, %85, %86, %87, %88, %89, %90, %91, %92, %93, %94, %95, %96, %97, %98, %99, %100, %101, %102, %103, %104, %105, %106, %107, %108, %109, %110, %111, %112, %113, %114, %115, %116, %117, %118, %119, %120, %121, %122, %123, %124, %125, %126, %127}, "
    "{%128, %129, %130, %131}, db, p, 1, 1, 0;\n"
    "}\n"
    : "+f"(d[0]), "+f"(d[1]), "+f"(d[2]), "+f"(d[3]), "+f"(d[4]), "+f"(d[5]), "+f"(d[6]), "+f"(d[7]), "+f"(d[8]), "+f"(d[9]), "+f"(d[10]), "+f"(d[11]), "+f"(d[12]), "+f"(d[13]), "+f"(d[14]), "+f"(d[15]), "+f"(d[16]), "+f"(d[17]), "+f"(d[18]), "+f"(d[19]), "+f"(d[20]), "+f"(d[21]), "+f"(d[22]), "+f"(d[23]), "+f"(d[24]), "+f"(d[25]), "+f"(d[26]), "+f"(d[27]), "+f"(d[28]), "+f"(d[29]), "+f"(d[30]), "+f"(d[31]), "+f"(d[32]), "+f"(d[33]), "+f"(d[34]), "+f"(d[35]), "+f"(d[36]), "+f"(d[37]), "+f"(d[38]), "+f"(d[39]), "+f"(d[40]), "+f"(d[41]), "+f"(d[42]), "+f"(d[43]), "+f"(d[44]), "+f"(d[45]), "+f"(d[46]), "+f"(d[47]), "+f"(d[48]), "+f"(d[49]), "+f"(d[50]), "+f"(d[51]), "+f"(d[52]), "+f"(d[53]), "+f"(d[54]), "+f"(d[55]), "+f"(d[56]), "+f"(d[57]), "+f"(d[58]), "+f"(d[59]), "+f"(d[60]), "+f"(d[61]), "+f"(d[62]), "+f"(d[63]), "+f"(d[64]), "+f"(d[65]), "+f"(d[66]), "+f"(d[67]), "+f"(d[68]), "+f"(d[69]), "+f"(d[70]), "+f"(d[71]), "+f"(d[72]), "+f"(d[73]), "+f"(d[74]), "+f"(d[75]), "+f"(d[76]), "+f"(d[77]), "+f"(d[78]), "+f"(d[79]), "+f"(d[80]), "+f"(d[81]), "+f"(d[82]), "+f"(d[83]), "+f"(d[84]), "+f"(d[85]), "+f"(d[86]), "+f"(d[87]), "+f"(d[88]), "+f"(d[89]), "+f"(d[90]), "+f"(d[91]), "+f"(d[92]), "+f"(d[93]), "+f"(d[94]), "+f"(d[95]), "+f"(d[96]), "+f"(d[97]), "+f"(d[98]), "+f"(d[99]), "+f"(d[100]), "+f"(d[101]), "+f"(d[102]), "+f"(d[103]), "+f"(d[104]), "+f"(d[105]), "+f"(d[106]), "+f"(d[107]), "+f"(d[108]), "+f"(d[109]), "+f"(d[110]), "+f"(d[111]), "+f"(d[112]), "+f"(d[113]), "+f"(d[114]), "+f"(d[115]), "+f"(d[116]), "+f"(d[117]), "+f"(d[118]), "+f"(d[119]), "+f"(d[120]), "+f"(d[121]), "+f"(d[122]), "+f"(d[123]), "+f"(d[124]), "+f"(d[125]), "+f"(d[126]), "+f"(d[127])
    : "r"(a[0]), "r"(a[1]), "r"(a[2]), "r"(a[3]), "r"(descB), "r"(accum));
}
template <> __device__ __forceinline__ void wgmma_rs<232>(float* d, const uint32_t* a, uint32_t descB, uint32_t accum) {
  asm volatile(
    "{\n.reg .pred p;\n.reg .b64 db;\n"
    "setp.ne.b32 p, %121, 0;\n"
    "mov.b64 db, {%120, 0x40000040};\n"
    "wgmma.mma_async.sync.aligned.m64n232k16.f32.bf16.bf16 "
    "{%0, %1, %2, %3, %4, %5, %6, %7, %8, %9, %10, %11, %12, %13, %14, %15, %16, %17, %18, %19, %20, %21, %22, %23, %24, %25, %26, %27, %28, %29, %30, %31, %32, %33, %34, %35, %36, %37, %38, %39, %40, %41, %42, %43, %44, %45, %46, %47, %48, %49, %50, %51, %52, %53, %54, %55, %56, %57, %58, %59, %60, %61, %62, %63, %64, %65, %66, %67, %68, %69, %70, %71, %72, %73, %74, %75, %76, %77, %78, %79, %80, %81, %82, %83, %84, %85, %86, %87, %88, %89, %90, %91, %92, %93, %94, %95, %96, %97, %98, %99, %100, %101, %102, %103, %104, %105, %106, %107, %108, %109, %110, %111, %112, %113, %114, %115}, "
    "{%116, %117, %118, %119}, db, p, 1, 1, 0;\n"
    "}\n"
    : "+f"(d[0]), "+f"(d[1]), "+f"(d[2]), "+f"(d[3]), "+f"(d[4]), "+f"(d[5]), "+f"(d[6]), "+f"(d[7]), "+f"(d[8]), "+f"(d[9]), "+f"(d[10]), "+f"(d[11]), "+f"(d[12]), "+f"(d[13]), "+f"(d[14]), "+f"(d[15]), "+f"(d[16]), "+f"(d[17]), "+f"(d[18]), "+f"(d[19]), "+f"(d[20]), "+f"(d[21]), "+f"(d[22]), "+f"(d[23]), "+f"(d[24]), "+f"(d[25]), "+f"(d[26]), "+f"(d[27]), "+f"(d[28]), "+f"(d[29]), "+f"(d[30]), "+f"(d[31]), "+f"(d[32]), "+f"(d[33]), "+f"(d[34]), "+f"(d[35]), "+f"(d[36]), "+f"(d[37]), "+f"(d[38]), "+f"(d[39]), "+f"(d[40]), "+f"(d[41]), "+f"(d[42]), "+f"(d[43]), "+f"(d[44]), "+f"(d[45]), "+f"(d[46]), "+f"(d[47]), "+f"(d[48]), "+f"(d[49]), "+f"(d[50]), "+f"(d[51]), "+f"(d[52]), "+f"(d[53]), "+f"(d[54]), "+f"(d[55]), "+f"(d[56]), "+f"(d[57]), "+f"(d[58]), "+f"(d[59]), "+f"(d[60]), "+f"(d[61]), "+f"(d[62]), "+f"(d[63]), "+f"(d[64]), "+f"(d[65]), "+f"(d[66]), "+f"(d[67]), "+f"(d[68]), "+f"(d[69]), "+f"(d[70]), "+f"(d[71]), "+f"(d[72]), "+f"(d[73]), "+f"(d[74]), "+f"(d[75]), "+f"(d[76]), "+f"(d[77]), "+f"(d[78]), "+f"(d[79]), "+f"(d[80]), "+f"(d[81]), "+f"(d[82]), "+f"(d[83]), "+f"(d[84]), "+f"(d[85]), "+f"(d[86]), "+f"(d[87]), "+f"(d[88]), "+f"(d[89]), "+f"(d[90]), "+f"(d[91]), "+f"(d[92]), "+f"(d[93]), "+f"(d[94]), "+f"(d[95]), "+f"(d[96]), "+f"(d[97]), "+f"(d[98]), "+f"(d[99]), "+f"(d[100]), "+f"(d[101]), "+f"(d[102]), "+f"(d[103]), "+f"(d[104]), "+f"(d[105]), "+f"(d[106]), "+f"(d[107]), "+f"(d[108]), "+f"(d[109]), "+f"(d[110]), "+f"(d[111]), "+f"(d[112]), "+f"(d[113]), "+f"(d[114]), "+f"(d[115])
    : "r"(a[0]), "r"(a[1]), "r"(a[2]), "r"(a[3]), "r"(descB), "r"(accum));
}
template <> __device__ __forceinline__ void wgmma_rs<40>(float* d, const uint32_t* a, uint32_t descB, uint32_t accum) {
  asm volatile(
    "{\n.reg .pred p;\n.reg .b64 db;\n"
    "setp.ne.b32 p, %25, 0;\n"
    "mov.b64 db, {%24, 0x40000040};\n"
    "wgmma.mma_async.sync.aligned.m64n40k16.f32.bf16.bf16 "
    "{%0, %1, %2, %3, %4, %5, %6, %7, %8, %9, %10, %11, %12, %13, %14, %15, %16, %17, %18, %19}, "
    "{%20, %21, %22, %23}, db, p, 1, 1, 0;\n"
    "}\n"
    : "+f"(d[0]), "+f"(d[1]), "+f"(d[2]), "+f"(d[3]), "+f"(d[4]), "+f"(d[5]), "+f"(d[6]), "+f"(d[7]), "+f"(d[8]), "+f"(d[9]), "+f"(d[10]), "+f"(d[11]), "+f"(d[12]), "+f"(d[13]), "+f"(d[14]), "+f"(d[15]), "+f"(d[16]), "+f"(d[17]), "+f"(d[18]), "+f"(d[19])
    : "r"(a[0]), "r"(a[1]), "r"(a[2]), "r"(a[3]), "r"(descB), "r"(accum));
}

template <int N> __device__ __forceinline__ void wgmma_rl(float* d, const uint32_t* a, uint64_t descB);
template <> __device__ __forceinline__ void wgmma_rl<48>(float* d, const uint32_t* a, uint64_t descB) {
  asm volatile(
    "wgmma.mma_async.sync.aligned.m64n48k16.f32.bf16.bf16 "
    "{%0, %1, %2, %3, %4, %5, %6, %7, %8, %9, %10, %11, %12, %13, %14, %15, %16, %17, %18, %19, %20, %21, %22, %23}, "
    "{%24, %25, %26, %27}, %28, 1, 1, 1, 0;\n"
    : "+f"(d[0]), "+f"(d[1]), "+f"(d[2]), "+f"(d[3]), "+f"(d[4]), "+f"(d[5]), "+f"(d[6]), "+f"(d[7]), "+f"(d[8]), "+f"(d[9]), "+f"(d[10]), "+f"(d[11]), "+f"(d[12]), "+f"(d[13]), "+f"(d[14]), "+f"(d[15]), "+f"(d[16]), "+f"(d[17]), "+f"(d[18]), "+f"(d[19]), "+f"(d[20]), "+f"(d[21]), "+f"(d[22]), "+f"(d[23])
    : "r"(a[0]), "r"(a[1]), "r"(a[2]), "r"(a[3]), "l"(descB));
}

template <int N> __device__ __forceinline__ void wgmma_ss(float* d, uint64_t descA, uint64_t descB, uint32_t accum);
template <> __device__ __forceinline__ void wgmma_ss<192>(float* d, uint64_t descA, uint64_t descB, uint32_t accum) {
  asm volatile(
    "{\n.reg .pred p;\n"
    "setp.ne.b32 p, %98, 0;\n"
    "wgmma.mma_async.sync.aligned.m64n192k16.f32.bf16.bf16 "
    "{%0, %1, %2, %3, %4, %5, %6, %7, %8, %9, %10, %11, %12, %13, %14, %15, %16, %17, %18, %19, %20, %21, %22, %23, %24, %25, %26, %27, %28, %29, %30, %31, %32, %33, %34, %35, %36, %37, %38, %39, %40, %41, %42, %43, %44, %45, %46, %47, %48, %49, %50, %51, %52, %53, %54, %55, %56, %57, %58, %59, %60, %61, %62, %63, %64, %65, %66, %67, %68, %69, %70, %71, %72, %73, %74, %75, %76, %77, %78, %79, %80, %81, %82, %83, %84, %85, %86, %87, %88, %89, %90, %91, %92, %93, %94, %95}, "
    "%96, %97, p, 1, 1, 0, 0;\n"
    "}\n"
    : "+f"(d[0]), "+f"(d[1]), "+f"(d[2]), "+f"(d[3]), "+f"(d[4]), "+f"(d[5]), "+f"(d[6]), "+f"(d[7]), "+f"(d[8]), "+f"(d[9]), "+f"(d[10]), "+f"(d[11]), "+f"(d[12]), "+f"(d[13]), "+f"(d[14]), "+f"(d[15]), "+f"(d[16]), "+f"(d[17]), "+f"(d[18]), "+f"(d[19]), "+f"(d[20]), "+f"(d[21]), "+f"(d[22]), "+f"(d[23]), "+f"(d[24]), "+f"(d[25]), "+f"(d[26]), "+f"(d[27]), "+f"(d[28]), "+f"(d[29]), "+f"(d[30]), "+f"(d[31]), "+f"(d[32]), "+f"(d[33]), "+f"(d[34]), "+f"(d[35]), "+f"(d[36]), "+f"(d[37]), "+f"(d[38]), "+f"(d[39]), "+f"(d[40]), "+f"(d[41]), "+f"(d[42]), "+f"(d[43]), "+f"(d[44]), "+f"(d[45]), "+f"(d[46]), "+f"(d[47]), "+f"(d[48]), "+f"(d[49]), "+f"(d[50]), "+f"(d[51]), "+f"(d[52]), "+f"(d[53]), "+f"(d[54]), "+f"(d[55]), "+f"(d[56]), "+f"(d[57]), "+f"(d[58]), "+f"(d[59]), "+f"(d[60]), "+f"(d[61]), "+f"(d[62]), "+f"(d[63]), "+f"(d[64]), "+f"(d[65]), "+f"(d[66]), "+f"(d[67]), "+f"(d[68]), "+f"(d[69]), "+f"(d[70]), "+f"(d[71]), "+f"(d[72]), "+f"(d[73]), "+f"(d[74]), "+f"(d[75]), "+f"(d[76]), "+f"(d[77]), "+f"(d[78]), "+f"(d[79]), "+f"(d[80]), "+f"(d[81]), "+f"(d[82]), "+f"(d[83]), "+f"(d[84]), "+f"(d[85]), "+f"(d[86]), "+f"(d[87]), "+f"(d[88]), "+f"(d[89]), "+f"(d[90]), "+f"(d[91]), "+f"(d[92]), "+f"(d[93]), "+f"(d[94]), "+f"(d[95])
    : "l"(descA), "l"(descB), "r"(accum));
}
template <> __device__ __forceinline__ void wgmma_ss<184>(float* d, uint64_t descA, uint64_t descB, uint32_t accum) {
  asm volatile(
    "{\n.reg .pred p;\n"
    "setp.ne.b32 p, %94, 0;\n"
    "wgmma.mma_async.sync.aligned.m64n184k16.f32.bf16.bf16 "
    "{%0, %1, %2, %3, %4, %5, %6, %7, %8, %9, %10, %11, %12, %13, %14, %15, %16, %17, %18, %19, %20, %21, %22, %23, %24, %25, %26, %27, %28, %29, %30, %31, %32, %33, %34, %35, %36, %37, %38, %39, %40, %41, %42, %43, %44, %45, %46, %47, %48, %49, %50, %51, %52, %53, %54, %55, %56, %57, %58, %59, %60, %61, %62, %63, %64, %65, %66, %67, %68, %69, %70, %71, %72, %73, %74, %75, %76, %77, %78, %79, %80, %81, %82, %83, %84, %85, %86, %87, %88, %89, %90, %91}, "
    "%92, %93, p, 1, 1, 0, 0;\n"
    "}\n"
    : "+f"(d[0]), "+f"(d[1]), "+f"(d[2]), "+f"(d[3]), "+f"(d[4]), "+f"(d[5]), "+f"(d[6]), "+f"(d[7]), "+f"(d[8]), "+f"(d[9]), "+f"(d[10]), "+f"(d[11]), "+f"(d[12]), "+f"(d[13]), "+f"(d[14]), "+f"(d[15]), "+f"(d[16]), "+f"(d[17]), "+f"(d[18]), "+f"(d[19]), "+f"(d[20]), "+f"(d[21]), "+f"(d[22]), "+f"(d[23]), "+f"(d[24]), "+f"(d[25]), "+f"(d[26]), "+f"(d[27]), "+f"(d[28]), "+f"(d[29]), "+f"(d[30]), "+f"(d[31]), "+f"(d[32]), "+f"(d[33]), "+f"(d[34]), "+f"(d[35]), "+f"(d[36]), "+f"(d[37]), "+f"(d[38]), "+f"(d[39]), "+f"(d[40]), "+f"(d[41]), "+f"(d[42]), "+f"(d[43]), "+f"(d[44]), "+f"(d[45]), "+f"(d[46]), "+f"(d[47]), "+f"(d[48]), "+f"(d[49]), "+f"(d[50]), "+f"(d[51]), "+f"(d[52]), "+f"(d[53]), "+f"(d[54]), "+f"(d[55]), "+f"(d[56]), "+f"(d[57]), "+f"(d[58]), "+f"(d[59]), "+f"(d[60]), "+f"(d[61]), "+f"(d[62]), "+f"(d[63]), "+f"(d[64]), "+f"(d[65]), "+f"(d[66]), "+f"(d[67]), "+f"(d[68]), "+f"(d[69]), "+f"(d[70]), "+f"(d[71]), "+f"(d[72]), "+f"(d[73]), "+f"(d[74]), "+f"(d[75]), "+f"(d[76]), "+f"(d[77]), "+f"(d[78]), "+f"(d[79]), "+f"(d[80]), "+f"(d[81]), "+f"(d[82]), "+f"(d[83]), "+f"(d[84]), "+f"(d[85]), "+f"(d[86]), "+f"(d[87]), "+f"(d[88]), "+f"(d[89]), "+f"(d[90]), "+f"(d[91])
    : "l"(descA), "l"(descB), "r"(accum));
}

template <int N> struct IC { static constexpr int v = N; };

__device__ __forceinline__ void stmatrix_x4_t(uint32_t addr, uint32_t r0, uint32_t r1, uint32_t r2, uint32_t r3) {
  asm volatile("stmatrix.sync.aligned.m8n8.x4.trans.shared.b16 [%0], {%1, %2, %3, %4};"
               ::"r"(addr), "r"(r0), "r"(r1), "r"(r2), "r"(r3) : "memory");
}
__device__ __forceinline__ void ldmatrix_x4(uint32_t* r, uint32_t addr) {
  asm volatile("ldmatrix.sync.aligned.m8n8.x4.shared.b16 {%0, %1, %2, %3}, [%4];"
               : "=r"(r[0]), "=r"(r[1]), "=r"(r[2]), "=r"(r[3]) : "r"(addr) : "memory");
}
__device__ __forceinline__ void ldmatrix_x4_if(uint32_t* r, uint32_t addr, uint32_t c) {
  asm volatile("{\n.reg .pred p;\nsetp.eq.u32 p, %5, 0;\n@p ldmatrix.sync.aligned.m8n8.x4.shared.b16 {%0, %1, %2, %3}, [%4];\n}\n"
               : "+r"(r[0]), "+r"(r[1]), "+r"(r[2]), "+r"(r[3]) : "r"(addr), "r"(c) : "memory");
}
__device__ __forceinline__ uint32_t pack_bf16(float a, float b) {
  __nv_bfloat162 v = __floats2bfloat162_rn(a, b);
  return *reinterpret_cast<uint32_t*>(&v);
}
__device__ __forceinline__ uint32_t prmt(uint32_t a, uint32_t b, uint32_t s) {
  uint32_t d;
  asm("prmt.b32 %0, %1, %2, %3;" : "=r"(d) : "r"(a), "r"(b), "r"(s));
  return d;
}
__device__ __forceinline__ uint32_t lds32(uint32_t a) {
  uint32_t v;
  asm volatile("ld.shared.u32 %0, [%1];" : "=r"(v) : "r"(a) : "memory");
  return v;
}
__device__ __forceinline__ void lds128(uint32_t* v, uint32_t a) {
  asm volatile("ld.shared.v4.u32 {%0, %1, %2, %3}, [%4];" : "=r"(v[0]), "=r"(v[1]), "=r"(v[2]), "=r"(v[3]) : "r"(a) : "memory");
}
__device__ __forceinline__ void sts128(uint32_t a, const uint32_t* v) {
  asm volatile("st.shared.v4.u32 [%0], {%1, %2, %3, %4};" ::"r"(a), "r"(v[0]), "r"(v[1]), "r"(v[2]), "r"(v[3]) : "memory");
}
__device__ __forceinline__ void sts32(uint32_t a, uint32_t v) {
  asm volatile("st.shared.u32 [%0], %1;" ::"r"(a), "r"(v) : "memory");
}
__device__ __forceinline__ void wait_until(uint32_t t0, uint32_t at) {
  asm volatile(
      "{\n.reg .pred p;\n.reg .s32 r;\n"
      "SPIN:\n"
      "mov.u32 r, %%clock;\n"
      "sub.s32 r, %0, r;\n"
      "setp.gt.s32 p, r, 0;\n"
      "shr.s32 r, r, %1;\n"
      "@p nanosleep.u32 r;\n"
      "@p bra.uni SPIN;\n}\n"
      ::"r"(t0 + at), "n"(NSH) : "memory");
}
__device__ __forceinline__ void spin_until(uint32_t t0, uint32_t at) {
  while ((uint32_t)clock() - t0 < at) {}
}
__device__ __forceinline__ void wait_count(const unsigned int* f, uint32_t& c) {
  asm volatile(
      "{\n.reg .pred p;\n.reg .u32 v;\n"
      "SPIN:\n"
      "ld.acquire.gpu.global.u32 v, [%1];\n"
      "add.u32 %0, %0, 16;\n"
      "setp.lt.u32 p, %0, 0x100000;\n"
      "setp.lt.and.u32 p, v, 64, p;\n"
      "@p nanosleep.u32 100;\n"
      "@p bra.uni SPIN;\n}\n"
      : "+r"(c) : "l"(f) : "memory");
}
template <int E>
__device__ __forceinline__ void ld_lut(uint32_t* v, const __nv_bfloat16* p) {
  asm volatile("ld.global.nc.u32 %0, [%1+%2];" : "=r"(v[E]) : "l"(p), "n"(((E & 3) * N_ + 8 * (E >> 2)) * 2));
  if constexpr (E < 7) ld_lut<E + 1>(v, p);
}
template <int OFF>
__device__ __forceinline__ void ld_codes4(uint32_t* w, const int* p) {
  asm volatile("ld.global.nc.L1::no_allocate.v4.u32 {%0, %1, %2, %3}, [%4+%5];" : "=r"(w[0]), "=r"(w[1]), "=r"(w[2]), "=r"(w[3]) : "l"(p), "n"(OFF));
}
__device__ __forceinline__ void ld_codes(uint32_t* w, const int* p) {
  ld_codes4<0>(w, p);
  ld_codes4<N_ * 4>(w + 4, p);
  ld_codes4<N_ * 32>(w + 8, p);
  ld_codes4<N_ * 36>(w + 12, p);
}
__device__ __forceinline__ void prefetch_map(const CUtensorMap* map) {
  asm volatile("prefetch.tensormap [%0];" ::"l"((uint64_t)map) : "memory");
}
template <int OFF>
__device__ __forceinline__ void ld_words(uint32_t* w, const uint8_t* p) {
  asm volatile("ld.relaxed.gpu.global.v4.u32 {%0, %1, %2, %3}, [%4+%5];" : "=r"(w[0]), "=r"(w[1]), "=r"(w[2]), "=r"(w[3]) : "l"(p), "n"(OFF) : "memory");
}
template <int OFF>
__device__ __forceinline__ void st_words(uint8_t* p, const uint32_t* w) {
  asm volatile("st.relaxed.gpu.global.v4.u32 [%0+%5], {%1, %2, %3, %4};" ::"l"(p), "r"(w[0]), "r"(w[1]), "r"(w[2]), "r"(w[3]), "n"(OFF) : "memory");
}

#define DBGR(i, j)
#define DBG(i)

__device__ __forceinline__ uint32_t word_key(uint32_t odd) { return 0xcdf00000u + (odd << 19); }
__device__ __forceinline__ uint32_t make_word(uint32_t c0, uint32_t c1, uint32_t c2, uint32_t c3, uint32_t key) {
  uint32_t p01, p23, n, w;
  asm("mad.lo.u32 %0, %1, 16, %2;" : "=r"(p01) : "r"(c1), "r"(c0));
  asm("mad.lo.u32 %0, %1, 16, %2;" : "=r"(p23) : "r"(c3), "r"(c2));
  asm("mad.lo.u32 %0, %1, 256, %2;" : "=r"(n) : "r"(p23), "r"(p01));
  asm("mad.lo.u32 %0, %1, 0x7fff, %2;" : "=r"(w) : "r"((n & 0x8888u) | key), "r"(n));
  return w;
}
struct Planes { uint32_t v[4][4]; };
__device__ __forceinline__ void lookup4(const Planes& pl, int c, uint32_t s, uint32_t sc, uint32_t& o0, uint32_t& o1) {
  uint32_t s2;
  asm("{\n.reg .b16 l, h;\n.reg .b32 t;\nmov.b32 {l, h}, %1;\nmov.b32 t, {h, h};\nmul.rn.f16x2 %0, t, %2;\n}\n" : "=r"(s2) : "r"(s), "r"(sc));
  const uint32_t lo = prmt(prmt(pl.v[0][2 * c], pl.v[1][2 * c], s), prmt(pl.v[2][2 * c], pl.v[3][2 * c], s), s2);
  const uint32_t hi = prmt(prmt(pl.v[0][2 * c + 1], pl.v[1][2 * c + 1], s), prmt(pl.v[2][2 * c + 1], pl.v[3][2 * c + 1], s), s2);
  o0 = prmt(lo, hi, 0x5140);
  o1 = prmt(lo, hi, 0x7362);
}
__device__ __forceinline__ void store_planes(uint32_t dst, const uint32_t* lv) {
#pragma unroll
  for (int h = 0; h < 2; h++) {
    uint32_t qp[4];
#pragma unroll
    for (int c = 0; c < 2; c++) {
      const uint32_t a = prmt(lv[4 * c], lv[4 * c + 1], h ? 0x7362 : 0x5140), b = prmt(lv[4 * c + 2], lv[4 * c + 3], h ? 0x7362 : 0x5140);
      qp[2 * c] = prmt(a, b, 0x5410);
      qp[2 * c + 1] = prmt(a, b, 0x7632);
    }
    sts128(dst + 64 * h, qp);
  }
}
__device__ __forceinline__ bool words_ok(const uint32_t* P, uint32_t tag) {
  return (P[0] & P[1] & P[2] & P[3] & P[4] & P[5] & P[6] & P[7] & tag) != 0;
}
template <int NJ>
__device__ __forceinline__ void stage_part(const float* a, uint32_t sts) {
#pragma unroll
  for (int j = 0; j < NJ; j++)
    stmatrix_x4_t(sts + 16 * j * 128, pack_bf16(a[8 * j], a[8 * j + 1]), pack_bf16(a[8 * j + 2], a[8 * j + 3]),
                  pack_bf16(a[8 * j + 4], a[8 * j + 5]), pack_bf16(a[8 * j + 6], a[8 * j + 7]));
}

template <int OFF>
__device__ __forceinline__ uint32_t lut_at(uint32_t tab, uint32_t c) {
  uint32_t v;
  asm volatile("ld.shared.u16 %0, [%1+%2];" : "=r"(v) : "r"(tab + 40 * c), "n"(OFF));
  return v;
}
template <int J>
__device__ __forceinline__ void convert_col(const uint32_t (*v)[4], uint32_t tab, uint8_t* dst) {
  uint32_t o[4];
#pragma unroll
  for (int i = 0; i < 4; i++) {
    const uint32_t a = lut_at<2 * J>(tab, v[2 * i][J]), b = lut_at<2 * J>(tab, v[2 * i + 1][J]);
    asm("mad.lo.u32 %0, %1, 65536, %2;" : "=r"(o[i]) : "r"(b), "r"(a));
  }
  st_words<2048 * J>(dst, o);
}

template <int J>
__device__ __forceinline__ void convert_shfl(const uint32_t (*v)[4], uint32_t e, uint8_t* dst) {
  uint32_t o[4];
#pragma unroll
  for (int i = 0; i < 4; i++) {
    uint32_t a, b;
    asm volatile("shfl.sync.idx.b32 %0, %1, %2, 0x101f, 0xffffffff;" : "=r"(a) : "r"(e), "r"(v[2 * i][J]));
    asm volatile("shfl.sync.idx.b32 %0, %1, %2, 0x101f, 0xffffffff;" : "=r"(b) : "r"(e), "r"(v[2 * i + 1][J]));
    o[i] = prmt(a, b, J & 1 ? 0x7632 : 0x5410);
  }
  st_words<2048 * J>(dst, o);
}

struct Maps { CUtensorMap m[NMAPS]; uint64_t desc; uint32_t tiles[66], jobs[396]; };
struct Tab { uint32_t tiles[66], jobs[396]; };
constexpr int imin(int a, int b) { return a < b ? a : b; }
constexpr Tab make_tab() {
  Tab m{};
  for (int t = 0; t < 66; t++) {
    const int u = t - 32, g = t < 32 ? t & 7 : 1 + u % 7, j = t < 32 ? t >> 3 : 4 + u / 7;
    int cl = t >= 60 ? (int)((0x413B3F394035ull >> (8 * (t - 60))) & 0xff) : g == 7 ? 48 + 2 * j : g ? 6 * j + g - 1 : imin(49 + 6 * j, 87 - 12 * j);
    if (GMAP == 0) cl = (t + 4) % 66;
    const int yi = cl / 6, fb = 2 * (cl % 6);
    const int fa = cl < 48 ? fb : 12 + 2 * (cl & 1), ta = cl < 48 ? TA * yi : imin(TC * ((cl - 48) >> 1), M_ - TC);
    m.tiles[t >= 62 ? t & 3 : t + 4] = fa | fb << 4 | ta << 5 | (TD * yi - (TB - TD) * imin(8 - yi, 0)) << 13;
  }
  int third[396] = {}, t2[396] = {}, by[896] = {}, nt = 0, na = 0;
  for (int i = 0; i < 396; i++) {
    third[i] = (m.tiles[i / 6] & 15) >= 12 && i % 3 < NB3;
    t2[i] = 1;
    nt += third[i];
  }
  const int need = 104 - nt;
  for (int b = 0, k = 0; b < 132; b++) {
    if ((m.tiles[b / 2] & 15) >= 12) continue;
    if ((na / 2 + 1) * need / 96 != (na / 2) * need / 96) {
      third[3 * b] = 1;
      if (k < 12) t2[3 * b] = 0;
      k++;
    }
    na++;
  }
  int u = 920, l = 0;
  for (int i = 0; i < 396; i++) {
    m.jobs[i] = third[i] ? u++ : 1024;
    by[third[i] ? m.jobs[i] - 128 : 396 + U0(i / 3, i % 3)] = i + 1;
  }
  for (int k = 0; k < 896; k++) {
    const int i = by[k] - 1;
    if (i < 0) continue;
    if (t2[i]) m.jobs[i] |= l << 11 | imin(LCAP, LT0 + l * LTS) / 8 << 20, l++;
    else m.jobs[i] |= 384 << 11;
  }
  return m;
}

#define TILES() \
  const int fta = (te & 15) + rank, ftb = ((te >> 4) & 15) + rank, toka = (te >> 5) & 0x7f8, tokb = (te >> 13) & 0x7f8; \
  const bool big = fta < 12; \
  (void)toka; (void)big; (void)tokb; (void)ftb
__global__ void __cluster_dims__(2, 1, 1) __launch_bounds__(NTHREADS, 1)
fused_kernel(unsigned int* __restrict__ count, const __nv_bfloat16* __restrict__ lut, uint8_t* __restrict__ gp,
             const int* __restrict__ qw, const uint8_t* __restrict__ xg, const __grid_constant__ Maps maps) {
  extern __shared__ __align__(1024) uint8_t smem_gen[];
  const uint32_t t0 = clock();
  const int tid = threadIdx.x;
  uint32_t cf[16];
  const int* src = qw + (((tid >> 8) * BK + 32 + (tid & 48) + ((tid >> 1) & 6)) * N_ + (blockIdx.x & 127) * 16 + (tid & 3) * 4);
  uint32_t ep0 = 0;
  if ((tid >> 6) == 2) {
    if (EPW) asm volatile("ld.relaxed.gpu.global.u32 %0, [%1];" : "=r"(ep0) : "l"(count) : "memory");
    ld_codes(cf, src);
  }
  const uint32_t te = maps.tiles[blockIdx.x >> 1];
  const int rank = blockIdx.x & 1;
  const uint32_t sl = smem_u32(smem_gen);
  auto bar = [&](int i) { return sl + OFF_BAR + 8 * i; };
  const int w12 = __shfl_sync(0xffffffffu, tid >> 5, 0);
  const int wg = w12 >> 2;
  const int warp = w12 & 3;
  const int lane = tid & 31;
  uint32_t bud = 0;
  if (__builtin_expect(wg == 0, 1)) {
    asm volatile("setmaxnreg.dec.sync.aligned.u32 72;");
    if (warp == 0) {
      if (lane == 0) {
#pragma unroll
        for (int i = 0; i < NBARS; i++) mbar_init(bar(i), i >= 4 && i < 8 ? 4 : 1);
        mbar_init(bar(B_LAST), 4);
        asm volatile("fence.mbarrier_init.release.cluster;" ::: "memory");
      }
      __syncwarp();
      cluster_arrive_relaxed();
      asm volatile("bar.arrive 4, 128;" ::: "memory");
      DBG(1);
      TILES();
      expect_w(bar(B_DIR), 2 * UNIT_BYTES);
      tma3_w(sl + 3 * STAGE_BYTES, &maps.m[M_D], bar(B_DIR), 0, 0, fta * 4);
      const int ca = TR1 && !big ? (TA - TC) * 128 : 0, cb = TR2 && big ? (TB - TD) * 128 : 0;
      const CUtensorMap *ma = &maps.m[M_XA + (ca ? rank : 0)], *mb = &maps.m[M_XB + (cb ? rank : 0)];
      expect_w(bar(B_FULL), X_BYTES - ca);
      cluster_wait();
      tma_mc_w(sl + rank * (X_BYTES / 2), ma, bar(B_FULL), 0, toka + rank * (TA / 2));
      DBG(2);
      expect_w(bar(B_LAST), SLAB_BYTES);
      wait_until(t0, XT0);
#pragma unroll 1
      for (int n = 1; n < 2 * KBLKS - 4; n++) {
        const int stage = n & 3;
        const bool first = n < KBLKS;
        const int rows = rank * (first ? TA / 2 : TB / 2);
        if (EXF) expect_w(bar(B_FULL + stage), STAGE_BYTES - (first ? ca : cb));
        mbar_wait(bar(B_EMPTY + stage), ((n - 3) >> 2) & 1, bud);
        if (!EXF) expect_w(bar(B_FULL + stage), STAGE_BYTES - (first ? ca : cb));
        tma_mc_w(sl + stage * STAGE_BYTES + rows * 128, first ? ma : mb, bar(B_FULL + stage),
                 (n & (KBLKS - 1)) * BK, (first ? toka : tokb) + rows);
        if (XPD && n >= XPS && n < KBLKS - XPD) {
          const uint8_t* a = xg + (((blockIdx.x & 127) * 16 + (lane >> 1)) * (K_ * 2) + (lane & 1) * 64 + (n + XPD) * 128);
          asm volatile("prefetch.global.L2 [%0];" ::"l"(a));
          if (!XPW) asm volatile("prefetch.global.L2 [%0+32];" ::"l"(a));
        }
        if (n <= KBLKS) {
          wait_until(t0, 32 * prmt((uint32_t)GATES, (uint32_t)(GATES >> 32), min(n, 7)));
          bulk_w(sl + ((n - 1) & 3) * STAGE_BYTES + X_BYTES, gp + (fta * KBLKS + n - 1) * SLAB_BYTES, SLAB_BYTES, bar(B_FULL + (n & 19)));
        }
        if (n == PN) wait_count(count + 32 * (1 + ((lds32(sl + OFF_EPOCH) & 256) ? 48 : 0) + 4 * ftb), bud);
        if (first) continue;
        if (n == KBLKS + 4 || n == KBLKS + 8) asm volatile("bar.sync %0, 64;" ::"r"(n & 8) : "memory");
        tma_w(sl + stage * STAGE_BYTES + TB * 128, &maps.m[M_W], bar(B_FULL + stage), (n - KBLKS) * BK, ftb * BF);
        tma_w(sl + stage * STAGE_BYTES + TB * 128 + 8192, &maps.m[M_W], bar(B_FULL + stage), (n - KBLKS) * BK, ftb * BF + 64);
      }
      const CUtensorMap *mx = &maps.m[M_XB], *mw = &maps.m[M_W];
      DBG(220);
      expect_w(bar(B_RDY), 16384);
      asm volatile("bar.sync 15, 96;" ::: "memory");
#pragma unroll
      for (int i = 0; i < 2; i++) {
        const uint32_t s = sl + i * STAGE_BYTES, w = sl + OFF_STG + 16384 + i * 32768, wb = bar(i ? B_FULL + 2 : B_RDY);
        if (i == 0) {
          tma_w(w, mw, wb, 12 * BK, ftb * BF + 64);
          tma_w(w + 8192, mw, wb, 13 * BK, ftb * BF + 64);
        }
        expect_w(bar(B_FULL + i), STAGE_BYTES);
        mbar_wait(bar(B_EMPTY + i), 0, bud);
        DBG(221 + i);
        tma_mc_w(s + rank * 12288, mx, bar(B_FULL + i), (12 + 2 * i + rank) * BK, tokb);
        tma_w(s + 24576, mw, bar(B_FULL + i), (12 + 2 * i) * BK, ftb * BF);
        tma_w(s + 32768, mw, bar(B_FULL + i), (13 + 2 * i) * BK, ftb * BF);
        if (i) {
          expect_w(wb, 16384);
          tma_w(w, mw, wb, (12 + 2 * i) * BK, ftb * BF + 64);
          tma_w(w + 8192, mw, wb, (13 + 2 * i) * BK, ftb * BF + 64);
        }
      }
      if (cb) mx++;
#pragma unroll
      for (int i = 2; i < 4; i++) {
        mbar_wait(bar(B_EMPTY + i), i & 1, bud);
        DBG(222 + i);
        if (i == 2) expect_w(bar(B_FULL + 3), 49152 - 4 * cb);
        tma_mc_w(sl + i * STAGE_BYTES + rank * 12288, mx, bar(B_FULL + 3), (8 + 2 * i + rank) * BK, tokb + TB / 2);
      }
      asm volatile(ELECT "@p red.relaxed.gpu.global.add.u32 [%0], %1;\n}\n" ::"l"(count), "r"(blockIdx.x < 2 * NUM_CTAS - 256 ? 1 : 2) : "memory");
    } else {
      const int p = warp - 1;
      uint32_t ep;
      asm volatile("ld.relaxed.gpu.global.u32 %0, [%1];" : "=r"(ep) : "l"(count) : "memory");
      cluster_arrive_relaxed();
      prefetch_map(&maps.m[p + (TR1 && p == 2 && (te & 15) >= 12 ? rank : 0)]);
      asm volatile("prefetch.global.L2 [%0];" ::"l"(xg + (((blockIdx.x * 16 + p * 8 + (lane >> 2)) & (M_ - 1)) * (K_ * 2) + (lane & 3) * 32)));
      const uint32_t so = OFF_STG + p * UNIT_BYTES;
      const uint32_t ua = sl + so + (lane & 3) * 256 + (((lane >> 2) ^ (2 * (lane & 3))) << 4);
      asm volatile("bar.sync 4, 128;" ::: "memory");
      if (!EPW && p == 2) {
        sts32(sl + OFF_EPOCH, ep);
        asm volatile("bar.arrive 1, 288;" ::: "memory");
      }
      int r = blockIdx.x, u = 128 + U0(r, p);
      const uint32_t job = maps.jobs[3 * r + p];
      uint32_t ph = 0, odd;
#pragma unroll 1
      do {
        wait_until(t0, D0 + (u - 128) * PU / 4);
        expect_w(bar(B_SLOT + p), UNIT_BYTES);
        tma_w(sl + so, &maps.m[M_Q], bar(B_SLOT + p), (u & 63) * 32, (u & ~63) + 32);
        DBG(16 + 8 * p + 2 * (r / NUM_CTAS));
        uint8_t* dst = gp + (((((u & 63) >> 2) * KBLKS + (u >> 6)) * 4 + (u & 3)) * 2048 + (lane >> 2) * 256 + (lane & 3) * 16);
        mbar_wait(bar(B_SLOT + p), ph, bud);
        asm volatile("and.b32 %0, %1, 256;" : "=r"(odd) : "r"(ep));
        DBG(184 + 4 * p + r / NUM_CTAS);
        uint32_t w[4][4];
#pragma unroll
        for (int b = 0; b < 4; b++) {
          uint32_t v[4][4];
          lds128(v[0], ua + b * 2048);
          lds128(v[1], (ua ^ 16) + b * 2048 + 128);
          lds128(v[2], ua + b * 2048 + 1024);
          lds128(v[3], (ua ^ 16) + b * 2048 + 1024 + 128);
#pragma unroll
          for (int j = 0; j < 4; j++) w[j][b] = make_word(v[0][j], v[1][j], v[2][j], v[3][j], word_key(odd));
        }
        st_words<0>(dst, w[0]); st_words<64>(dst, w[1]); st_words<128>(dst, w[2]); st_words<192>(dst, w[3]);
        __syncwarp();
        DBG(17 + 8 * p + 2 * (r / NUM_CTAS));
        ph ^= 1;
        r += NUM_CTAS;
        u = ph ? u + 3 * NUM_CTAS : job & 2047;
      } while (u < 1024);
      const int l = (job >> 11) & 511;
      const int ls = (l * 1366) >> 16, cg = l - 48 * ls;
      unsigned int* cnt = count + (32 + 6 * __shfl_sync(0xffffffffu, odd, 0));
      prefetch_map(&maps.m[M_XB + p]);
      prefetch_map(&maps.m[M_Q2]);
      if (l < 384) {
        uint32_t e[8];
        const __nv_bfloat16* s = lut + ((lane & 15) * N_ + 2048 + cg * 32 + (lane & 16));
        asm volatile("ld.global.nc.v4.u32 {%0, %1, %2, %3}, [%4];" : "=r"(e[0]), "=r"(e[1]), "=r"(e[2]), "=r"(e[3]) : "l"(s));
        asm volatile("ld.global.nc.v4.u32 {%0, %1, %2, %3}, [%4+16];" : "=r"(e[4]), "=r"(e[5]), "=r"(e[6]), "=r"(e[7]) : "l"(s));
        wait_until(t0, (job >> 20) * 8);
        expect_w(bar(B_SLOT + p), 2 * UNIT_BYTES);
        tma3_w(sl + so, &maps.m[M_Q2], bar(B_SLOT + p), 2048 + cg * 32, ls * 16, 0);
        tma3_w(sl + so + 32768, &maps.m[M_Q2], bar(B_SLOT + p), 2048 + cg * 32, ls * 16, 4);
        DBG(22 + 8 * p);
        uint32_t tab = sl + OFF_TAB + p * 1536 + (SHF ? lane * 32 : (lane >> 4) * 644);
        if (SHF) {
          sts128(tab, e);
          sts128(tab + 16, e + 4);
        } else {
#pragma unroll
          for (int i = 0; i < 8; i++) sts32(tab + (lane & 15) * 40 + 4 * i, e[i]);
          __syncwarp();
        }
        uint8_t* dst = gp + (W_OFF + cg * 65536 + ls * 256 + (lane >> 4) * 32768 + (lane & 15) * 16);
        const uint32_t src = sl + so + (lane & 15) * 128 + ((((lane >> 2) & 4) ^ (lane & 7)) << 4);
        mbar_wait(bar(B_SLOT + p), ph, bud);
#pragma unroll 1
        for (int c = 0; c < 64; c += 16, tab += 8, dst += 8192) {
          uint32_t v[8][4];
#pragma unroll
          for (int i = 0; i < 8; i++) lds128(v[i], (src ^ c) + (i & 3) * 2048 + (i >> 2) * 32768);
          if (SHF) {
            asm volatile("ld.shared.v2.u32 {%0, %1}, [%2];" : "=r"(e[0]), "=r"(e[1]) : "r"(tab) : "memory");
            convert_shfl<0>(v, e[0], dst);
            convert_shfl<1>(v, e[0], dst);
            convert_shfl<2>(v, e[1], dst);
            convert_shfl<3>(v, e[1], dst);
          } else {
          convert_col<0>(v, tab, dst);
          convert_col<1>(v, tab, dst);
          convert_col<2>(v, tab, dst);
          convert_col<3>(v, tab, dst);
          }
        }
        __syncwarp();
        DBG(23 + 8 * p);
      }
      arrive_w(bar(B_LAST));
      if (l < 384)
        asm volatile(ELECT "@p fence.proxy.async.global;\n@p red.release.gpu.global.add.u32 [%0], %1;\n}\n"
                     ::"l"(cnt + 32 * ((cg & ~3) + min(ls >> 1, 2))), "r"(ls < 4 ? 8 : 4) : "memory");
      cluster_wait();
      TILES();
      prefetch_map(&maps.m[p ? M_O32 : M_W]);
      if (p > 0) {
        asm volatile("bar.sync %0, 160;" ::"r"(12 + p) : "memory");
        if (FEN) asm volatile("fence.proxy.async.shared::cta;" ::: "memory");
        uint32_t t1 = clock();
#pragma unroll 1
        for (int i = 0; i < TA; i += OB, t1 += PC * OB / 32) {
          wait_until(t1, 0);
          const int rr = min(i ^ 128, (big ? TA : TC) - OB);
          if (i == 128) {
            bulk_wait_read();
            asm volatile("bar.arrive 15, 96;" ::: "memory");
          }
          store_w(&maps.m[M_O32], sl + OFF_STG + (p - 1) * 32768 + rr * 128, fta * BF + 64 * (p - 1), toka + rr);
        }
        bulk_wait_read();
        DBG(227 + p);
        asm volatile("bar.arrive %0, 160;" ::"r"(12 + p) : "memory");
        const uint32_t sg = sl + OFF_STG + (p - 1) * 32768;
        const int c0 = 2048 + ftb * BF + 64 * (p - 1);
        uint32_t ids = p == 1 ? 0x0126 : 0x8437;
#pragma unroll 2
        for (int k = 0; k < 4; k++, ids >>= 4) {
          const int r = 48 * (k ^ 1), r2 = min(r + 24, (big ? TD : TB) - 24);
          asm volatile("bar.sync %0, 160;" ::"r"(ids & 15) : "memory");
          asm volatile("fence.proxy.async.shared::cta;" ::: "memory");
          store_w(&maps.m[M_O24], sg + r * 128, c0, tokb + r);
          store_w(&maps.m[M_O24], sg + r2 * 128, c0, tokb + r2);
        }
        bulk_wait_read();
      } else {
        if (blockIdx.x < 48) count[32 * (50 + blockIdx.x) - (cnt - count)] = 0;
#pragma unroll 1
        for (int i = 1; i < 3; i++) {
          wait_count(cnt + 32 * (4 * ftb + i), bud);
          asm volatile("bar.arrive %0, 64;" ::"r"(8 * i - 8) : "memory");
        }
      }
    }
    asm volatile("exit;");
  }
  const int cw = wg - 1;
  TILES();
  cluster_arrive_relaxed();
  if (warp >= 2) {
    ld_lut<0>(cf, lut + (fta * BF + 4 * (lane & 3) * N_ + 64 * cw + 32 * (warp & 1) + (lane & 16) + ((lane >> 1) & 6)));
  } else if (cw) {
    spin_until(t0, S1D);
    ld_codes(cf, src);
  } else if (EPW) {
    sts32(sl + OFF_EPOCH, ep0);
    asm volatile("bar.arrive 1, 256;" ::: "memory");
  }
  if (EPW) {
    if (w12 >= 6) asm volatile("bar.sync 1, 256;" ::: "memory");
  } else asm volatile("bar.sync 1, 288;" ::: "memory");
  const uint32_t odd = lds32(sl + OFF_EPOCH) & 256;
  DBG(40 + w12);
  if (warp >= 2) store_planes(sl + OFF_PL + cw * 32768 + (warp & 1) * 1024 + (lane & 28) * 32 + (lane & 3) * 16, cf);
  else {
    uint8_t* dst = gp + (((blockIdx.x & 120) * 2 + cw) * SLAB_BYTES + (blockIdx.x & 7) * 1024 + (tid & 63) * 16);
    const uint32_t tb = sl + OFF_STG + 61440 + cw * 1024;
#pragma unroll
    for (int j = 0; j < 4; j++)
      sts32(tb + (lane & 3) * 256 + j * 64 + (lane & 12) * 4 + ((tid >> 2) & 12), make_word(cf[j], cf[4 + j], cf[8 + j], cf[12 + j], word_key(odd)));
    asm volatile("bar.sync %0, 64;" ::"r"(6 + cw) : "memory");
    lds128(cf, tb + (tid & 63) * 16);
    st_words<0>(dst, cf);
  }
  DBG(52 + w12);
  asm volatile("setmaxnreg.inc.sync.aligned.u32 216;");
  uint32_t rel = (tid & 127) < 2 ? mapa(bar(B_EMPTY), lane) : 0u;
  uint32_t tg = (w12 - 4) * 1024 + lane * 16;
  uint32_t tw = sl + X_BYTES + tg;
  const uint8_t* gt = gp + (tg + fta * KBLKS * SLAB_BYTES);
  uint32_t tag = (1u << 28) - (odd << 19), sc = 0x3c00 + 8 * odd;
  asm volatile("" : "+r"(tw), "+l"(gt), "+r"(rel), "+r"(tag), "+r"(sc));
  Planes pl;
  uint32_t A[16], P[8];
  float acc[TA / 2];
  DBG(64 + cw);
  if (PLF) {
  asm volatile("bar.sync %0, 128;" ::"r"(2 + cw) : "memory");
#pragma unroll
  for (int k = 0; k < 4; k++) lds128(pl.v[k], sl + OFF_PL + cw * 32768 + (tid & 124) * 16 + 16 * k);
  }
  {
    const uint32_t td = sl + 3 * STAGE_BYTES - 8192 + (w12 >> 1) * 4096 + (lane & 3) * 256 + ((((tid >> 3) & 4) ^ (lane >> 4) ^ (2 * (lane & 3))) << 4) + (lane & 12);
    mbar_wait(bar(B_DIR), 0, bud);
    DBG(88 + cw);
#pragma unroll
    for (int k = 0; k < 4; k++) {
      const uint32_t a = (td ^ ((k & 2) << 4)) + (k & 1) * 2048;
      P[2 + (k & 1) + 2 * (k & 2)] = make_word(lds32(a), lds32((a ^ 16) + 128), lds32(a + 1024), lds32((a ^ 16) + 1152), word_key(odd));
    }
  }
  if (!PLF) {
  asm volatile("bar.sync %0, 128;" ::"r"(2 + cw) : "memory");
#pragma unroll
  for (int k = 0; k < 4; k++) lds128(pl.v[k], sl + OFF_PL + cw * 32768 + (tid & 124) * 16 + 16 * k);
  }
  mbar_wait(bar(B_FULL), 0, bud);
  DBG(66 + cw);
  auto tile1 = [&](auto nh) {
    uint32_t d = UD, dn, fb = bar(B_FULL + 1), pa = 0;
#pragma unroll 1
    for (int n = 0; n < KBLKS; n++) {
      bool ok;
#pragma unroll
      for (int b = 0; b < 4; b++) {
        const int m = n + 1;
        if (b == WB && !EP1) mbar_wait_fast(fb, (m >> 2) & 1, bud);
        if (b == WB && EP1 == 1 && !ok) mbar_wait(fb, (m >> 2) & 1, bud);
        if (b == 1 && EP1 == 3) ok = mbar_test(fb, (m >> 2) & 1);
        if (b == 1 && EP1 == 5) ok = mbar_peek(fb, (m >> 2) & 1);
        if (b == 2 && EP1 >= 4 && __builtin_expect(!ok, 0)) {
          mbar_wait(fb, (m >> 2) & 1, bud);
          lds128(P, tw + pa);
          lds128(P + 4, tw + pa + 512);
        }
        if (b == 2) {
#pragma unroll 1
          while (__builtin_expect(!words_ok(P, tag), 0)) {
            if ((bud += 16) >= 0x100000) break;
            asm volatile("{\n.reg .u64 a;\nmad.wide.u32 a, %8, 8192, %9;\nld.relaxed.gpu.global.v4.u32 {%0, %1, %2, %3}, [a];\n"
                         "ld.relaxed.gpu.global.v4.u32 {%4, %5, %6, %7}, [a+512];\n}\n"
                         : "=r"(P[0]), "=r"(P[1]), "=r"(P[2]), "=r"(P[3]), "=r"(P[4]), "=r"(P[5]), "=r"(P[6]), "=r"(P[7]) : "r"(n), "l"(gt) : "memory");
          }
          __syncwarp();
        }
        lookup4(pl, 0, P[b ^ 2], sc, A[4 * b], A[4 * b + 2]);
        lookup4(pl, 1, P[4 + (b ^ 2)], sc, A[4 * b + 1], A[4 * b + 3]);
        if (b == 1) {
          if ((EP1 == 2 || EP1 == 3) && !ok) mbar_wait(fb, (m >> 2) & 1, bud);
          lds128(P, tw + pa);
          lds128(P + 4, tw + pa + 512);
        }
        if (b == 3) {
          asm volatile("mad.lo.u32 %0, %1, %3, %2;" : "=r"(dn) : "r"(m & 3), "r"(UD), "n"(STAGE_BYTES / 16));
          asm volatile("mad.lo.u32 %0, %1, 8, %2;" : "=r"(fb) : "r"((m + 1) & 19), "r"(bar(B_FULL)));
          asm volatile("mul.lo.u32 %0, %1, %2;" : "=r"(pa) : "r"(m & 3), "n"(STAGE_BYTES));
        }
        if (((WD >> (4 * b)) & 3) == 1) wgmma_wait<1>();
        if (((WD >> (4 * b)) & 3) == 2) wgmma_wait<2>();
        if (b == RB) mbar_arrive_remote_if(rel + 8 * ((n - 1) & 3), rel);
        if (b == S1B && n == S1N && cw == 1) asm volatile("bar.sync 9, 256;" ::: "memory");
        if (b == 0 && (EP1 == 1 || EP1 == 2)) ok = mbar_test(fb, (m >> 2) & 1);
        if (b == 0 && EP1 == 4) ok = mbar_peek(fb, (m >> 2) & 1);
        wgmma_fence();
        wgmma_rs<decltype(nh)::v>(acc, A + 4 * b, d + 2 * b, b > 0 || n != 0);
        wgmma_commit();
      }
      d = dn;
    }
  };
  if (big) tile1(IC<TA>()); else tile1(IC<TC>());
  if (cw != 1) asm volatile("bar.arrive 9, 256;" ::: "memory");
  const uint32_t stg = sl + OFF_STG + cw * 32768;
  const uint32_t so8 = stg + ((lane & 7) + ((lane >> 4) << 3)) * 128 + (((2 * warp + ((lane >> 3) & 1)) ^ (lane & 7)) << 4);
  DBG(212 + cw);
  mbar_wait(bar(B_FULL), 0, bud);
  DBG(214 + cw);
  if (NP > 1 && !W17) mbar_wait(bar(B_FULL + 1), 0, bud);
  DBG(216 + cw);
  const uint64_t ub = maps.desc, ua = ub + (TB * 8 + cw * 512);
  wgmma_wait<0>();
  mbar_arrive_remote_if(rel + 24, rel);
  fence_regs(acc);
  DBGR(0, 68 + cw);
  {
    uint32_t o[64];
#pragma unroll
    for (int k = 0; k < 48; k++) o[k] = pack_bf16(acc[2 * k], acc[2 * k + 1]);
#pragma unroll
    for (int k = 0; k < 48; k++) asm volatile("" : "+r"(o[k]) :: "memory");
    DBG(92 + cw);
    wgmma_fence();
#pragma unroll
    for (int b = 0; b < 4 * NP; b++) {
      const int so = (b >> 2) * (STAGE_BYTES / 16) + 2 * (b & 3);
      if (b == 4 && W17) mbar_wait(bar(B_FULL + 1), 0, bud);
      wgmma_ss<TB>(acc, ua + so, ub + so, b != 0);
      if ((b & 3) == 3 || b == 4) wgmma_commit();
      if (b == 0) {
#pragma unroll
        for (int k = 48; k < 64; k++) o[k] = pack_bf16(acc[2 * k], acc[2 * k + 1]);
      }
      if (b == 4) {
        wgmma_wait<1>();
        mbar_arrive_remote_if(rel, rel);
      }
#pragma unroll
      for (int j = 0; j < 16; j++)
        if (j * NSB / 16 + SB0 == b) stmatrix_x4_t(so8 + j * 2048, o[4 * j], o[4 * j + 1], o[4 * j + 2], o[4 * j + 3]);
    }
  }
  if (!FEN) asm volatile("fence.proxy.async.shared::cta;" ::: "memory");
  asm volatile("bar.arrive %0, 160;" ::"r"(13 + cw) : "memory");
  cluster_wait();
  DBG(70 + cw);
  auto tile2 = [&](auto nt) {
#pragma unroll 1
    for (int n = NP; n < KBLKS - 4; n++) {
      const uint32_t so = (n & 3) * (STAGE_BYTES / 16);
      mbar_wait_fast(bar(B_FULL) + 8 * (n & 3), (n >> 2) & 1, bud);
      wgmma_fence();
      wgmma_ss<decltype(nt)::v>(acc, ua + so, ub + so, 1);
      wgmma_commit();
      wgmma_wait<1>();
      mbar_arrive_remote_if(rel + 8 * ((n - 1) & 3), rel);
#pragma unroll
      for (int b = 1; b < 4; b++) wgmma_ss<decltype(nt)::v>(acc, ua + so + 2 * b, ub + so + 2 * b, 1);
      wgmma_commit();
    }
  };
  if (big) tile2(IC<TD>()); else tile2(IC<TB>());
  uint32_t W[64];
  float c2[TB / 2];
  DBGR(1, 72 + cw);
  const uint32_t wa = sl + (warp * 16 + (lane & 15)) * 128 + (((lane >> 4) ^ (lane & 7)) << 4);
  const uint32_t w0 = wa + (cw ? OFF_STG + 16384 : 24576), w2 = wa + (cw ? OFF_STG + 49152 : STAGE_BYTES + 24576);
  auto ldw = [&](int b) { ldmatrix_x4(W + 4 * b, ((b & 8 ? w2 : w0) ^ ((b & 3) << 5)) + ((b >> 2) & 1) * 8192); };
  const uint32_t b2 = bar(B_FULL + 1 + cw);
  mbar_wait(bar(cw ? B_RDY : B_FULL), 1, bud);
  if (cw) DBG(226);
#pragma unroll
  for (int b = 0; b < PF; b++) ldw(b);
  bool ok = mbar_peek(b2, 1);
  wgmma_wait<0>();
  mbar_arrive_remote_if(rel + 24, rel);
  if (cw) {
    mbar_wait(b2, 1, bud);
    ok = true;
    DBG(227);
#pragma unroll
    for (int b = 8; b < UA; b++) ldw(b);
  }
#pragma unroll
  for (int k = 0; k < TB / 2; k++) asm volatile("mov.b32 %0, %1;" : "=f"(c2[k]) : "f"(acc[k]) : "memory");
#pragma unroll
  for (int h = 0; h < 2; h++) {
    constexpr int L = 48;
    if (h) mbar_wait(bar(B_FULL + 3), 1, bud);
    if (h || cw) asm volatile("bar.sync %0, 256;" ::"r"(9 + 2 * h + cw) : "memory");
    DBGR(2 + 3 * h, 74 + 6 * h + cw);
    auto part = [&](auto nn) {
#pragma unroll
      for (int i = 0; i < 16; i++) {
        if (h ? i >= QD1 && i <= QN1 : i >= QD0 && i <= QN0) {
          if (h) wgmma_wait<QD1 - 1>(); else wgmma_wait<QD0 - 1>();
        }
        if (i == 0 || (h == 0 && ((FM0 >> i) & 1))) wgmma_fence();
        const int off = ((2 * h + (i >> 3)) * STAGE_BYTES + ((i >> 2) & 1) * 12288 + L * 128) / 16 + 2 * (i & 3);
        if constexpr (decltype(nn)::v == TB / 2 - L) wgmma_rl<decltype(nn)::v>(c2 + 48 * h + L / 2, W + 4 * i, ub + off);
        else wgmma_rs<decltype(nn)::v>(c2 + 48 * h + L / 2, W + 4 * i, UD + off, 1);
        if (h == 0 && i < IX) wgmma_rl<L>(c2, W + 4 * i, ub + off - L * 8);
        if (i < (h ? QN1 : QN0) || (!h && i == NA)) wgmma_commit();
        if (h == 0) {
#pragma unroll
          for (int e = 0; e < LPS; e++) {
            const int j = (i - LD0) * LPS + PF + e;
            if (j == 8 && !ok) mbar_wait(b2, 1, bud);
            if (j >= PF && j < UA) ldmatrix_x4_if(W + 4 * j, (w2 ^ ((j & 3) << 5)) + ((j >> 2) & 1) * 8192, cw);
            else if (j >= PF && j < 16) ldw(j);
          }
        }
      }
      wgmma_commit();
    };
    if (h && big) part(IC<TD - TB / 2 - L>()); else part(IC<TB / 2 - L>());
    const int k0 = h ? K0 : K00 + IX;
    if (h) wgmma_fence();
#pragma unroll
    for (int i = h ? 0 : IX; i < 16; i++) {
      const int off = ((2 * h + (i >> 3)) * STAGE_BYTES + ((i >> 2) & 1) * 12288) / 16 + 2 * (i & 3);
      wgmma_rl<L>(c2 + 48 * h, W + 4 * i, ub + off);
      if (i == k0 - 1) {
        wgmma_commit();
        if (!h) asm volatile("bar.sync %0, 160;" ::"r"(13 + cw) : "memory");
        if (!h) {
          wgmma_wait<2>();
          asm volatile("bar.arrive %0, 256;" ::"r"(10 + cw) : "memory");
        }
        wgmma_wait<1>();
#pragma unroll
        for (int k = L / 2; k < 48; k++) asm volatile("" : "+f"(c2[48 * h + k]) :: "memory");
        if (h == TCH) DBGR(8, 218 + cw);
      }
      const int j = i - k0 + 1 + L / 16;
      if (i >= k0 - 1 && j < 6) stage_part<1>(c2 + 48 * h + 8 * j, so8 + 16 * 128 * (6 * h + j));
      if (j == 5) asm volatile("bar.arrive %0, 160;" ::"r"(h ? 1 + 3 * cw : 6 + cw) : "memory");
    }
    wgmma_commit();
    if (h) asm volatile("{\n.reg .pred p;\nsetp.eq.u32 p, %0, 0;\n@p bar.arrive 12, 256;\n}\n" ::"r"(cw) : "memory");
    if (h == TCH) DBGR(9, 230 + cw);
    wgmma_wait<0>();
#pragma unroll
    for (int k = 0; k < L / 2; k++) asm volatile("" : "+f"(c2[48 * h + k]) :: "memory");
    DBGR(3 + 3 * h, 76 + 6 * h + cw);
    stage_part<L / 16>(c2 + 48 * h, so8 + 96 * 128 * h);
    asm volatile("bar.arrive %0, 160;" ::"r"(h ? 8 * cw : 2 + cw) : "memory");
    DBGR(4 + 3 * h, 78 + 6 * h + cw);
  }
}

typedef CUresult (*EncodeFn)(CUtensorMap*, CUtensorMapDataType, cuuint32_t, void*, const cuuint64_t*, const cuuint64_t*,
                             const cuuint32_t*, const cuuint32_t*, CUtensorMapInterleave, CUtensorMapSwizzle,
                             CUtensorMapL2promotion, CUtensorMapFloatOOBfill);

}

extern "C" void kernel_launch(void* const* d_in, const int* in_sizes, int n_in, void* d_out, int out_size) {
  const __nv_bfloat16* x = (const __nv_bfloat16*)d_in[0];
  const int* qw = (const int*)d_in[1];
  const __nv_bfloat16* lut = (const __nv_bfloat16*)d_in[2];

  static EncodeFn enc = nullptr;
  static unsigned int* count = nullptr;
  static uint8_t* gp = nullptr;
  if (!enc) {
    cudaDriverEntryPointQueryResult q;
    void* fn = nullptr;
    cudaGetDriverEntryPoint("cuTensorMapEncodeTiled", &fn, cudaEnableDefault, &q);
    enc = (EncodeFn)fn;
    cudaGetSymbolAddress((void**)&count, g_count);
    cudaGetSymbolAddress((void**)&gp, g_p);
    cudaFuncSetAttribute(fused_kernel, cudaFuncAttributeMaxDynamicSharedMemorySize, SMEM_BYTES);
  }
  Maps maps;
  const cuuint32_t es[3] = {1, 1, 1};
  auto map2 = [&](int i, CUtensorMapDataType t, const void* p, int d0, int d1, int bytes, int b0, int b1, CUtensorMapL2promotion pr) {
    cuuint64_t dims[2] = {(cuuint64_t)d0, (cuuint64_t)d1};
    cuuint64_t strides[1] = {(cuuint64_t)d0 * bytes};
    cuuint32_t box[2] = {(cuuint32_t)b0, (cuuint32_t)b1};
    enc(&maps.m[i], t, 2, (void*)p, dims, strides, box, es, CU_TENSOR_MAP_INTERLEAVE_NONE, CU_TENSOR_MAP_SWIZZLE_128B, pr, CU_TENSOR_MAP_FLOAT_OOB_FILL_NONE);
  };
  map2(M_XA, CU_TENSOR_MAP_DATA_TYPE_BFLOAT16, x, K_, M_, 2, BK, TA / 2, XPROM);
  map2(M_XC, CU_TENSOR_MAP_DATA_TYPE_BFLOAT16, x, K_, M_, 2, BK, TC - TA / 2, XPROM);
  map2(M_XD, CU_TENSOR_MAP_DATA_TYPE_BFLOAT16, x, K_, M_, 2, BK, TD - TB / 2, XPROM);
  map2(M_XB, CU_TENSOR_MAP_DATA_TYPE_BFLOAT16, x, K_, M_, 2, BK, TB / 2, XPROM);
  map2(M_O24, CU_TENSOR_MAP_DATA_TYPE_BFLOAT16, d_out, N_, M_, 2, 64, 24, CU_TENSOR_MAP_L2_PROMOTION_NONE);
  map2(M_O32, CU_TENSOR_MAP_DATA_TYPE_BFLOAT16, d_out, N_, M_, 2, 64, OB, CU_TENSOR_MAP_L2_PROMOTION_NONE);
  map2(M_Q, CU_TENSOR_MAP_DATA_TYPE_INT32, qw, N_, K_, 4, 32, BK, QPROM);
  map2(M_W, CU_TENSOR_MAP_DATA_TYPE_BFLOAT16, gp + W_OFF, K_, N_ - 2048, 2, BK, 64, XPROM);
  {
    cuuint64_t dims[3] = {(cuuint64_t)N_, (cuuint64_t)K_ / 8, 8};
    cuuint64_t strides[2] = {(cuuint64_t)N_ * 32, (cuuint64_t)N_ * 4};
    cuuint32_t box[3] = {32, 16, 4};
    enc(&maps.m[M_Q2], CU_TENSOR_MAP_DATA_TYPE_INT32, 3, (void*)qw, dims, strides, box, es, CU_TENSOR_MAP_INTERLEAVE_NONE,
        CU_TENSOR_MAP_SWIZZLE_128B, QPROM, CU_TENSOR_MAP_FLOAT_OOB_FILL_NONE);
  }
  {
    cuuint64_t dims[3] = {32, (cuuint64_t)K_, (cuuint64_t)N_ / 32};
    cuuint64_t strides[2] = {(cuuint64_t)N_ * 4, 128};
    cuuint32_t box[3] = {32, 32, 4};
    enc(&maps.m[M_D], CU_TENSOR_MAP_DATA_TYPE_INT32, 3, (void*)qw, dims, strides, box, es, CU_TENSOR_MAP_INTERLEAVE_NONE,
        CU_TENSOR_MAP_SWIZZLE_128B, QPROM, CU_TENSOR_MAP_FLOAT_OOB_FILL_NONE);
  }
  maps.desc = (0x40000040ull << 32) + UD;
  constexpr Tab tab = make_tab();
  for (int t = 0; t < 66; t++) maps.tiles[t] = tab.tiles[t];
  for (int i = 0; i < 396; i++) maps.jobs[i] = tab.jobs[i];
  fused_kernel<<<NUM_CTAS, NTHREADS, SMEM_BYTES, cudaStreamPerThread>>>(count, lut, gp, qw, (const uint8_t*)x, maps);
}
```

```cpp
#include <cuda_runtime.h>
#include <cuda_bf16.h>
#include <cuda.h>
#include <stdint.h>
#include <cstdio>
#include <algorithm>

namespace {

constexpr int M_ = 2048, K_ = 1024, N_ = 3584;
constexpr int BF = 128, BK = 64;
constexpr int TA = 256, TB = 192;
#define TCC 232
constexpr int TC = TCC, TD = 184;
constexpr int STAGES = 4;
constexpr int KBLKS = K_ / BK;
constexpr int X_BYTES = TA * BK * 2;
constexpr int UNIT_BYTES = BK * 32 * 4;
constexpr int SLAB_BYTES = BF * BK;
constexpr int STAGE_BYTES = X_BYTES + SLAB_BYTES;
constexpr int OFF_STG = STAGES * STAGE_BYTES;
constexpr int OFF_PL = OFF_STG + 3 * UNIT_BYTES;
constexpr int OFF_TAB = OFF_PL + 2048;
constexpr int OFF_BAR = OFF_STG + 65536;
constexpr int W_OFF = 16 * KBLKS * SLAB_BYTES;
constexpr int SMEM_BYTES = OFF_BAR + 512;
constexpr int NUM_CTAS = 132;
constexpr int NTHREADS = 384;
constexpr int NPACK = 3;
#define XT0 1400
#define WT0 2350
#define WTS 1000
#define S1D 400
#define PC 900
#define OB 32
#define WD 0x2212
#define RB 1
#define D0 600
#define WB 1
#define LT0 7800
#define LTS 13
#define XPROM CU_TENSOR_MAP_L2_PROMOTION_L2_128B
#define QPROM CU_TENSOR_MAP_L2_PROMOTION_L2_128B
#define S1B 1
#define S1N 15
#define NP 3
#define PN 16
#define EP1 1
#define W17 1
#define SB0 0
#define NSB 8
#define FEN 1
#define GMAP 1
#define EPW 1
#define LCAP 14000
#define NB3 1
#define ORD 1
#define PU 36
#define U0(r, p) (ORD == 0 ? 3 * (r) + (p) : ORD == 1 ? 132 * (p) + (r) : (p) ? 131 + 2 * (r) + (p) : (r))
#define G0 WT0
#define G1 (WT0 + WTS)
#define G2 (WT0 + 2 * WTS)
#define G3 (WT0 + 3 * WTS)
#define G4 (WT0 + 4 * WTS)
#define G5 (WT0 + 5 * WTS)
constexpr uint64_t GATES = (uint64_t)(G0 / 32) << 8 | (uint64_t)(G1 / 32) << 16 | (uint64_t)(G2 / 32) << 24 | (uint64_t)(G3 / 32) << 32 | (uint64_t)(G4 / 32) << 40 | (uint64_t)(G5 / 32) << 48;
#define TR1 1
#define TR2 1
#define SW 0
#define XPD 2
#define XPS 2
#define XPW 1
#define SHF 1
#define PLF 1
#define EXF 1
#define PF 8
#define LD0 0
#define LPS 2
#define QD1 5
#define QN1 12
#define K0 4
#define QD0 3
#define QN0 8
#define FM0 0x100
#define K00 4
#define TCH 0
#define IX 8
#define UH 2
#define NA 13
#define UA 16
#define BF1 1
#define NTB 12
#define GB 7
#define W128 1
#define WP 0
#define RM 0x12
#define SMK 0xbaa9877654432110ull
#define SJ 0
#define DUP 1
#define T3 1
#define QD3 7
#define QN3 15
#define K3 6
#define HI 10
#define R24 0
#define UH3 1
#define K4 8
#define AD 2
#define BO 1
#define PEEL 0
#define TL 1
#define SLC 1
#define PADN 0
#define SWP 1
#define U0A 16
#define PKI -2
#define EW 1
#define TCN 12
#define WI 7
#define NSH 2
static_assert(SMEM_BYTES <= 232448, "smem");
static_assert(TB * 128 + 2 * SLAB_BYTES == STAGE_BYTES, "stage");
constexpr int B_FULL = 0, B_EMPTY = 4, B_DIR = 8, B_SLOT = 9, NBARS = 12, B_LAST = 16, B_RDY = B_DIR, B_W = 17;
constexpr int OFF_EPOCH = OFF_BAR + 8 * NBARS;
constexpr uint32_t SB = 1024;
constexpr uint32_t UD = (SB >> 4) | (1u << 16);
enum { M_Q, M_D, M_XA, M_XC, M_XB, M_XD, M_O24, M_O32, M_O48, M_W, M_Q2, M_W2, NMAPS };

__device__ __align__(1024) uint8_t g_p[W_OFF + 12 * KBLKS * 2 * SLAB_BYTES];
__device__ __align__(128) unsigned int g_count[32 * 97];

__device__ __forceinline__ uint32_t smem_u32(const void* p) { return (uint32_t)__cvta_generic_to_shared(p); }
__device__ __forceinline__ void mbar_init(uint32_t bar, uint32_t cnt) {
  asm volatile("mbarrier.init.shared::cta.b64 [%0], %1;" ::"r"(bar), "r"(cnt) : "memory");
}
__device__ __forceinline__ void mbar_wait(uint32_t bar, uint32_t parity, uint32_t& c) {
  asm volatile(
      "{\n.reg .pred p;\n"
      "SPIN:\n"
      "mbarrier.try_wait.parity.shared::cta.b64 p, [%1], %2;\n"
      "add.u32 %0, %0, 1;\n"
      "setp.ge.or.u32 p, %0, 0x100000, p;\n"
      "@!p bra.uni SPIN;\n}\n"
      : "+r"(c) : "r"(bar), "r"(parity) : "memory");
}
__device__ __forceinline__ void mbar_wait_fast(uint32_t bar, uint32_t parity, uint32_t& c) {
  asm volatile(
      "{\n.reg .pred p;\n"
      "SPIN:\n"
      "mbarrier.try_wait.parity.shared::cta.b64 p, [%1], %2;\n"
      "@p bra.uni DONE;\n"
      "add.u32 %0, %0, 1;\n"
      "setp.lt.u32 p, %0, 0x100000;\n"
      "@p bra.uni SPIN;\n"
      "DONE:\n}\n"
      : "+r"(c) : "r"(bar), "r"(parity) : "memory");
}
__device__ __forceinline__ bool mbar_test(uint32_t bar, uint32_t parity) {
  uint32_t ok;
  asm volatile("{\n.reg .pred p;\nmbarrier.try_wait.parity.shared::cta.b64 p, [%1], %2;\nselp.u32 %0, 1, 0, p;\n}\n" : "=r"(ok) : "r"(bar), "r"(parity) : "memory");
  return ok != 0;
}
__device__ __forceinline__ bool mbar_peek(uint32_t bar, uint32_t parity) {
  uint32_t ok;
  asm volatile("{\n.reg .pred p;\nmbarrier.test_wait.parity.shared::cta.b64 p, [%1], %2;\nselp.u32 %0, 1, 0, p;\n}\n" : "=r"(ok) : "r"(bar), "r"(parity) : "memory");
  return ok != 0;
}
__device__ __forceinline__ void mbar_arrive(uint32_t bar) {
  asm volatile("mbarrier.arrive.shared::cta.b64 _, [%0];" ::"r"(bar) : "memory");
}
__device__ __forceinline__ uint32_t mapa(uint32_t a, uint32_t cta) {
  uint32_t r;
  asm("mapa.shared::cluster.u32 %0, %1, %2;" : "=r"(r) : "r"(a), "r"(cta));
  return r;
}
__device__ __forceinline__ void mbar_arrive_remote_if(uint32_t ra, uint32_t cond) {
  asm volatile("{\n.reg .pred p;\nsetp.ne.u32 p, %1, 0;\n@p mbarrier.arrive.shared::cluster.b64 _, [%0];\n}\n" ::"r"(ra), "r"(cond) : "memory");
}
#define ELECT "{\n.reg .pred p;\nelect.sync _|p, 0xffffffff;\n"
__device__ __forceinline__ void expect_w(uint32_t bar, uint32_t bytes) {
  asm volatile(ELECT "@p mbarrier.arrive.expect_tx.shared::cta.b64 _, [%0], %1;\n}\n" ::"r"(bar), "r"(bytes) : "memory");
}
__device__ __forceinline__ void arrive_w(uint32_t bar) {
  asm volatile(ELECT "@p mbarrier.arrive.shared::cta.b64 _, [%0];\n}\n" ::"r"(bar) : "memory");
}
__device__ __forceinline__ void tma_mc_w(uint32_t dst, const CUtensorMap* map, uint32_t bar, int c0, int c1) {
  asm volatile(
      ELECT "@p cp.async.bulk.tensor.2d.shared::cluster.global.mbarrier::complete_tx::bytes.multicast::cluster [%0], [%1, {%3, %4}], [%2], %5;\n}\n"
      ::"r"(dst), "l"((uint64_t)map), "r"(bar), "r"(c0), "r"(c1), "h"((uint16_t)3) : "memory");
}
__device__ __forceinline__ void wait_tma_mc_w(uint32_t wb, uint32_t parity, uint32_t& c, uint32_t dst, const CUtensorMap* map, uint32_t bar, int c0, int c1) {
  asm volatile(
      "{\n.reg .pred p;\n"
      "SPIN:\n"
      "mbarrier.try_wait.parity.shared::cta.b64 p, [%1], %2;\n"
      "add.u32 %0, %0, 1;\n"
      "setp.ge.or.u32 p, %0, 0x100000, p;\n"
      "@!p bra.uni SPIN;\n"
      "elect.sync _|p, 0xffffffff;\n"
      "@p cp.async.bulk.tensor.2d.shared::cluster.global.mbarrier::complete_tx::bytes.multicast::cluster [%3], [%4, {%6, %7}], [%5], %8;\n}\n"
      : "+r"(c) : "r"(wb), "r"(parity), "r"(dst), "l"((uint64_t)map), "r"(bar), "r"(c0), "r"(c1), "h"((uint16_t)3) : "memory");
}
__device__ __forceinline__ void bulk_w(uint32_t dst, const void* src, uint32_t bytes, uint32_t bar) {
  asm volatile(ELECT "@p cp.async.bulk.shared::cluster.global.mbarrier::complete_tx::bytes [%0], [%1], %2, [%3];\n}\n"
               ::"r"(dst), "l"(src), "r"(bytes), "r"(bar) : "memory");
}
__device__ __forceinline__ void tma_w(uint32_t dst, const CUtensorMap* map, uint32_t bar, int c0, int c1) {
  asm volatile(
      ELECT "@p cp.async.bulk.tensor.2d.shared::cluster.global.mbarrier::complete_tx::bytes [%0], [%1, {%3, %4}], [%2];\n}\n"
      ::"r"(dst), "l"((uint64_t)map), "r"(bar), "r"(c0), "r"(c1) : "memory");
}
__device__ __forceinline__ void tma3_w(uint32_t dst, const CUtensorMap* map, uint32_t bar, int c0, int c1, int c2) {
  asm volatile(
      ELECT "@p cp.async.bulk.tensor.3d.shared::cluster.global.mbarrier::complete_tx::bytes [%0], [%1, {%3, %4, %5}], [%2];\n}\n"
      ::"r"(dst), "l"((uint64_t)map), "r"(bar), "r"(c0), "r"(c1), "r"(c2) : "memory");
}
__device__ __forceinline__ void store_w(const CUtensorMap* map, uint32_t src, int c0, int c1) {
  asm volatile(ELECT "@p cp.async.bulk.tensor.2d.global.shared::cta.bulk_group [%0, {%2, %3}], [%1];\n}\n"
               "cp.async.bulk.commit_group;"
               ::"l"((uint64_t)map), "r"(src), "r"(c0), "r"(c1) : "memory");
}
__device__ __forceinline__ void bulk_wait_read() { asm volatile("cp.async.bulk.wait_group.read 0;" ::: "memory"); }
__device__ __forceinline__ void cluster_arrive_relaxed() { asm volatile("barrier.cluster.arrive.relaxed.aligned;" ::: "memory"); }
__device__ __forceinline__ void cluster_wait() { asm volatile("barrier.cluster.wait.acquire.aligned;" ::: "memory"); }
__device__ __forceinline__ void wgmma_fence() { asm volatile("wgmma.fence.sync.aligned;" ::: "memory"); }
__device__ __forceinline__ void wgmma_commit() { asm volatile("wgmma.commit_group.sync.aligned;" ::: "memory"); }
template <int N> __device__ __forceinline__ void wgmma_wait() { asm volatile("wgmma.wait_group.sync.aligned %0;" ::"n"(N) : "memory"); }
template <int N> __device__ __forceinline__ void fence_regs(float (&p)[N]) {
#pragma unroll
  for (int i = 0; i < N; i++) asm volatile("" : "+f"(p[i]) :: "memory");
}

template <int N> __device__ __forceinline__ void wgmma_rs(float* d, const uint32_t* a, uint32_t descB, uint32_t accum);
template <> __device__ __forceinline__ void wgmma_rs<256>(float* d, const uint32_t* a, uint32_t descB, uint32_t accum) {
  asm volatile(
    "{\n.reg .pred p;\n.reg .b64 db;\n"
    "setp.ne.b32 p, %133, 0;\n"
    "mov.b64 db, {%132, 0x40000040};\n"
    "wgmma.mma_async.sync.aligned.m64n256k16.f32.bf16.bf16 "
    "{%0, %1, %2, %3, %4, %5, %6, %7, %8, %9, %10, %11, %12, %13, %14, %15, %16, %17, %18, %19, %20, %21, %22, %23, %24, %25, %26, %27, %28, %29, %30, %31, %32, %33, %34, %35, %36, %37, %38, %39, %40, %41, %42, %43, %44, %45, %46, %47, %48, %49, %50, %51, %52, %53, %54, %55, %56, %57, %58, %59, %60, %61, %62, %63, %64, %65, %66, %67, %68, %69, %70, %71, %72, %73, %74, %75, %76, %77, %78, %79, %80, %81, %82, %83, %84, %85, %86, %87, %88, %89, %90, %91, %92, %93, %94, %95, %96, %97, %98, %99, %100, %101, %102, %103, %104, %105, %106, %107, %108, %109, %110, %111, %112, %113, %114, %115, %116, %117, %118, %119, %120, %121, %122, %123, %124, %125, %126, %127}, "
    "{%128, %129, %130, %131}, db, p, 1, 1, 0;\n"
    "}\n"
    : "+f"(d[0]), "+f"(d[1]), "+f"(d[2]), "+f"(d[3]), "+f"(d[4]), "+f"(d[5]), "+f"(d[6]), "+f"(d[7]), "+f"(d[8]), "+f"(d[9]), "+f"(d[10]), "+f"(d[11]), "+f"(d[12]), "+f"(d[13]), "+f"(d[14]), "+f"(d[15]), "+f"(d[16]), "+f"(d[17]), "+f"(d[18]), "+f"(d[19]), "+f"(d[20]), "+f"(d[21]), "+f"(d[22]), "+f"(d[23]), "+f"(d[24]), "+f"(d[25]), "+f"(d[26]), "+f"(d[27]), "+f"(d[28]), "+f"(d[29]), "+f"(d[30]), "+f"(d[31]), "+f"(d[32]), "+f"(d[33]), "+f"(d[34]), "+f"(d[35]), "+f"(d[36]), "+f"(d[37]), "+f"(d[38]), "+f"(d[39]), "+f"(d[40]), "+f"(d[41]), "+f"(d[42]), "+f"(d[43]), "+f"(d[44]), "+f"(d[45]), "+f"(d[46]), "+f"(d[47]), "+f"(d[48]), "+f"(d[49]), "+f"(d[50]), "+f"(d[51]), "+f"(d[52]), "+f"(d[53]), "+f"(d[54]), "+f"(d[55]), "+f"(d[56]), "+f"(d[57]), "+f"(d[58]), "+f"(d[59]), "+f"(d[60]), "+f"(d[61]), "+f"(d[62]), "+f"(d[63]), "+f"(d[64]), "+f"(d[65]), "+f"(d[66]), "+f"(d[67]), "+f"(d[68]), "+f"(d[69]), "+f"(d[70]), "+f"(d[71]), "+f"(d[72]), "+f"(d[73]), "+f"(d[74]), "+f"(d[75]), "+f"(d[76]), "+f"(d[77]), "+f"(d[78]), "+f"(d[79]), "+f"(d[80]), "+f"(d[81]), "+f"(d[82]), "+f"(d[83]), "+f"(d[84]), "+f"(d[85]), "+f"(d[86]), "+f"(d[87]), "+f"(d[88]), "+f"(d[89]), "+f"(d[90]), "+f"(d[91]), "+f"(d[92]), "+f"(d[93]), "+f"(d[94]), "+f"(d[95]), "+f"(d[96]), "+f"(d[97]), "+f"(d[98]), "+f"(d[99]), "+f"(d[100]), "+f"(d[101]), "+f"(d[102]), "+f"(d[103]), "+f"(d[104]), "+f"(d[105]), "+f"(d[106]), "+f"(d[107]), "+f"(d[108]), "+f"(d[109]), "+f"(d[110]), "+f"(d[111]), "+f"(d[112]), "+f"(d[113]), "+f"(d[114]), "+f"(d[115]), "+f"(d[116]), "+f"(d[117]), "+f"(d[118]), "+f"(d[119]), "+f"(d[120]), "+f"(d[121]), "+f"(d[122]), "+f"(d[123]), "+f"(d[124]), "+f"(d[125]), "+f"(d[126]), "+f"(d[127])
    : "r"(a[0]), "r"(a[1]), "r"(a[2]), "r"(a[3]), "r"(descB), "r"(accum));
}
template <> __device__ __forceinline__ void wgmma_rs<232>(float* d, const uint32_t* a, uint32_t descB, uint32_t accum) {
  asm volatile(
    "{\n.reg .pred p;\n.reg .b64 db;\n"
    "setp.ne.b32 p, %121, 0;\n"
    "mov.b64 db, {%120, 0x40000040};\n"
    "wgmma.mma_async.sync.aligned.m64n232k16.f32.bf16.bf16 "
    "{%0, %1, %2, %3, %4, %5, %6, %7, %8, %9, %10, %11, %12, %13, %14, %15, %16, %17, %18, %19, %20, %21, %22, %23, %24, %25, %26, %27, %28, %29, %30, %31, %32, %33, %34, %35, %36, %37, %38, %39, %40, %41, %42, %43, %44, %45, %46, %47, %48, %49, %50, %51, %52, %53, %54, %55, %56, %57, %58, %59, %60, %61, %62, %63, %64, %65, %66, %67, %68, %69, %70, %71, %72, %73, %74, %75, %76, %77, %78, %79, %80, %81, %82, %83, %84, %85, %86, %87, %88, %89, %90, %91, %92, %93, %94, %95, %96, %97, %98, %99, %100, %101, %102, %103, %104, %105, %106, %107, %108, %109, %110, %111, %112, %113, %114, %115}, "
    "{%116, %117, %118, %119}, db, p, 1, 1, 0;\n"
    "}\n"
    : "+f"(d[0]), "+f"(d[1]), "+f"(d[2]), "+f"(d[3]), "+f"(d[4]), "+f"(d[5]), "+f"(d[6]), "+f"(d[7]), "+f"(d[8]), "+f"(d[9]), "+f"(d[10]), "+f"(d[11]), "+f"(d[12]), "+f"(d[13]), "+f"(d[14]), "+f"(d[15]), "+f"(d[16]), "+f"(d[17]), "+f"(d[18]), "+f"(d[19]), "+f"(d[20]), "+f"(d[21]), "+f"(d[22]), "+f"(d[23]), "+f"(d[24]), "+f"(d[25]), "+f"(d[26]), "+f"(d[27]), "+f"(d[28]), "+f"(d[29]), "+f"(d[30]), "+f"(d[31]), "+f"(d[32]), "+f"(d[33]), "+f"(d[34]), "+f"(d[35]), "+f"(d[36]), "+f"(d[37]), "+f"(d[38]), "+f"(d[39]), "+f"(d[40]), "+f"(d[41]), "+f"(d[42]), "+f"(d[43]), "+f"(d[44]), "+f"(d[45]), "+f"(d[46]), "+f"(d[47]), "+f"(d[48]), "+f"(d[49]), "+f"(d[50]), "+f"(d[51]), "+f"(d[52]), "+f"(d[53]), "+f"(d[54]), "+f"(d[55]), "+f"(d[56]), "+f"(d[57]), "+f"(d[58]), "+f"(d[59]), "+f"(d[60]), "+f"(d[61]), "+f"(d[62]), "+f"(d[63]), "+f"(d[64]), "+f"(d[65]), "+f"(d[66]), "+f"(d[67]), "+f"(d[68]), "+f"(d[69]), "+f"(d[70]), "+f"(d[71]), "+f"(d[72]), "+f"(d[73]), "+f"(d[74]), "+f"(d[75]), "+f"(d[76]), "+f"(d[77]), "+f"(d[78]), "+f"(d[79]), "+f"(d[80]), "+f"(d[81]), "+f"(d[82]), "+f"(d[83]), "+f"(d[84]), "+f"(d[85]), "+f"(d[86]), "+f"(d[87]), "+f"(d[88]), "+f"(d[89]), "+f"(d[90]), "+f"(d[91]), "+f"(d[92]), "+f"(d[93]), "+f"(d[94]), "+f"(d[95]), "+f"(d[96]), "+f"(d[97]), "+f"(d[98]), "+f"(d[99]), "+f"(d[100]), "+f"(d[101]), "+f"(d[102]), "+f"(d[103]), "+f"(d[104]), "+f"(d[105]), "+f"(d[106]), "+f"(d[107]), "+f"(d[108]), "+f"(d[109]), "+f"(d[110]), "+f"(d[111]), "+f"(d[112]), "+f"(d[113]), "+f"(d[114]), "+f"(d[115])
    : "r"(a[0]), "r"(a[1]), "r"(a[2]), "r"(a[3]), "r"(descB), "r"(accum));
}
template <> __device__ __forceinline__ void wgmma_rs<40>(float* d, const uint32_t* a, uint32_t descB, uint32_t accum) {
  asm volatile(
    "{\n.reg .pred p;\n.reg .b64 db;\n"
    "setp.ne.b32 p, %25, 0;\n"
    "mov.b64 db, {%24, 0x40000040};\n"
    "wgmma.mma_async.sync.aligned.m64n40k16.f32.bf16.bf16 "
    "{%0, %1, %2, %3, %4, %5, %6, %7, %8, %9, %10, %11, %12, %13, %14, %15, %16, %17, %18, %19}, "
    "{%20, %21, %22, %23}, db, p, 1, 1, 0;\n"
    "}\n"
    : "+f"(d[0]), "+f"(d[1]), "+f"(d[2]), "+f"(d[3]), "+f"(d[4]), "+f"(d[5]), "+f"(d[6]), "+f"(d[7]), "+f"(d[8]), "+f"(d[9]), "+f"(d[10]), "+f"(d[11]), "+f"(d[12]), "+f"(d[13]), "+f"(d[14]), "+f"(d[15]), "+f"(d[16]), "+f"(d[17]), "+f"(d[18]), "+f"(d[19])
    : "r"(a[0]), "r"(a[1]), "r"(a[2]), "r"(a[3]), "r"(descB), "r"(accum));
}
template <> __device__ __forceinline__ void wgmma_rs<32>(float* d, const uint32_t* a, uint32_t descB, uint32_t accum) {
  asm volatile(
    "{\n.reg .pred p;\n.reg .b64 db;\n"
    "setp.ne.b32 p, %21, 0;\n"
    "mov.b64 db, {%20, 0x40000040};\n"
    "wgmma.mma_async.sync.aligned.m64n32k16.f32.bf16.bf16 "
    "{%0, %1, %2, %3, %4, %5, %6, %7, %8, %9, %10, %11, %12, %13, %14, %15}, "
    "{%16, %17, %18, %19}, db, p, 1, 1, 0;\n"
    "}\n"
    : "+f"(d[0]), "+f"(d[1]), "+f"(d[2]), "+f"(d[3]), "+f"(d[4]), "+f"(d[5]), "+f"(d[6]), "+f"(d[7]), "+f"(d[8]), "+f"(d[9]), "+f"(d[10]), "+f"(d[11]), "+f"(d[12]), "+f"(d[13]), "+f"(d[14]), "+f"(d[15])
    : "r"(a[0]), "r"(a[1]), "r"(a[2]), "r"(a[3]), "r"(descB), "r"(accum));
}
template <> __device__ __forceinline__ void wgmma_rs<24>(float* d, const uint32_t* a, uint32_t descB, uint32_t accum) {
  asm volatile(
    "{\n.reg .pred p;\n.reg .b64 db;\n"
    "setp.ne.b32 p, %17, 0;\n"
    "mov.b64 db, {%16, 0x40000040};\n"
    "wgmma.mma_async.sync.aligned.m64n24k16.f32.bf16.bf16 "
    "{%0, %1, %2, %3, %4, %5, %6, %7, %8, %9, %10, %11}, "
    "{%12, %13, %14, %15}, db, p, 1, 1, 0;\n"
    "}\n"
    : "+f"(d[0]), "+f"(d[1]), "+f"(d[2]), "+f"(d[3]), "+f"(d[4]), "+f"(d[5]), "+f"(d[6]), "+f"(d[7]), "+f"(d[8]), "+f"(d[9]), "+f"(d[10]), "+f"(d[11])
    : "r"(a[0]), "r"(a[1]), "r"(a[2]), "r"(a[3]), "r"(descB), "r"(accum));
}

template <int N> __device__ __forceinline__ void wgmma_rl(float* d, const uint32_t* a, uint64_t descB);
template <> __device__ __forceinline__ void wgmma_rl<48>(float* d, const uint32_t* a, uint64_t descB) {
  asm volatile(
    "wgmma.mma_async.sync.aligned.m64n48k16.f32.bf16.bf16 "
    "{%0, %1, %2, %3, %4, %5, %6, %7, %8, %9, %10, %11, %12, %13, %14, %15, %16, %17, %18, %19, %20, %21, %22, %23}, "
    "{%24, %25, %26, %27}, %28, 1, 1, 1, 0;\n"
    : "+f"(d[0]), "+f"(d[1]), "+f"(d[2]), "+f"(d[3]), "+f"(d[4]), "+f"(d[5]), "+f"(d[6]), "+f"(d[7]), "+f"(d[8]), "+f"(d[9]), "+f"(d[10]), "+f"(d[11]), "+f"(d[12]), "+f"(d[13]), "+f"(d[14]), "+f"(d[15]), "+f"(d[16]), "+f"(d[17]), "+f"(d[18]), "+f"(d[19]), "+f"(d[20]), "+f"(d[21]), "+f"(d[22]), "+f"(d[23])
    : "r"(a[0]), "r"(a[1]), "r"(a[2]), "r"(a[3]), "l"(descB));
}
template <> __device__ __forceinline__ void wgmma_rl<32>(float* d, const uint32_t* a, uint64_t descB) {
  asm volatile(
    "wgmma.mma_async.sync.aligned.m64n32k16.f32.bf16.bf16 "
    "{%0, %1, %2, %3, %4, %5, %6, %7, %8, %9, %10, %11, %12, %13, %14, %15}, "
    "{%16, %17, %18, %19}, %20, 1, 1, 1, 0;\n"
    : "+f"(d[0]), "+f"(d[1]), "+f"(d[2]), "+f"(d[3]), "+f"(d[4]), "+f"(d[5]), "+f"(d[6]), "+f"(d[7]), "+f"(d[8]), "+f"(d[9]), "+f"(d[10]), "+f"(d[11]), "+f"(d[12]), "+f"(d[13]), "+f"(d[14]), "+f"(d[15])
    : "r"(a[0]), "r"(a[1]), "r"(a[2]), "r"(a[3]), "l"(descB));
}
template <> __device__ __forceinline__ void wgmma_rl<24>(float* d, const uint32_t* a, uint64_t descB) {
  asm volatile(
    "wgmma.mma_async.sync.aligned.m64n24k16.f32.bf16.bf16 "
    "{%0, %1, %2, %3, %4, %5, %6, %7, %8, %9, %10, %11}, "
    "{%12, %13, %14, %15}, %16, 1, 1, 1, 0;\n"
    : "+f"(d[0]), "+f"(d[1]), "+f"(d[2]), "+f"(d[3]), "+f"(d[4]), "+f"(d[5]), "+f"(d[6]), "+f"(d[7]), "+f"(d[8]), "+f"(d[9]), "+f"(d[10]), "+f"(d[11])
    : "r"(a[0]), "r"(a[1]), "r"(a[2]), "r"(a[3]), "l"(descB));
}

template <int N> __device__ __forceinline__ void wgmma_ss(float* d, uint64_t descA, uint64_t descB, uint32_t accum);
template <> __device__ __forceinline__ void wgmma_ss<192>(float* d, uint64_t descA, uint64_t descB, uint32_t accum) {
  asm volatile(
    "{\n.reg .pred p;\n"
    "setp.ne.b32 p, %98, 0;\n"
    "wgmma.mma_async.sync.aligned.m64n192k16.f32.bf16.bf16 "
    "{%0, %1, %2, %3, %4, %5, %6, %7, %8, %9, %10, %11, %12, %13, %14, %15, %16, %17, %18, %19, %20, %21, %22, %23, %24, %25, %26, %27, %28, %29, %30, %31, %32, %33, %34, %35, %36, %37, %38, %39, %40, %41, %42, %43, %44, %45, %46, %47, %48, %49, %50, %51, %52, %53, %54, %55, %56, %57, %58, %59, %60, %61, %62, %63, %64, %65, %66, %67, %68, %69, %70, %71, %72, %73, %74, %75, %76, %77, %78, %79, %80, %81, %82, %83, %84, %85, %86, %87, %88, %89, %90, %91, %92, %93, %94, %95}, "
    "%96, %97, p, 1, 1, 0, 0;\n"
    "}\n"
    : "+f"(d[0]), "+f"(d[1]), "+f"(d[2]), "+f"(d[3]), "+f"(d[4]), "+f"(d[5]), "+f"(d[6]), "+f"(d[7]), "+f"(d[8]), "+f"(d[9]), "+f"(d[10]), "+f"(d[11]), "+f"(d[12]), "+f"(d[13]), "+f"(d[14]), "+f"(d[15]), "+f"(d[16]), "+f"(d[17]), "+f"(d[18]), "+f"(d[19]), "+f"(d[20]), "+f"(d[21]), "+f"(d[22]), "+f"(d[23]), "+f"(d[24]), "+f"(d[25]), "+f"(d[26]), "+f"(d[27]), "+f"(d[28]), "+f"(d[29]), "+f"(d[30]), "+f"(d[31]), "+f"(d[32]), "+f"(d[33]), "+f"(d[34]), "+f"(d[35]), "+f"(d[36]), "+f"(d[37]), "+f"(d[38]), "+f"(d[39]), "+f"(d[40]), "+f"(d[41]), "+f"(d[42]), "+f"(d[43]), "+f"(d[44]), "+f"(d[45]), "+f"(d[46]), "+f"(d[47]), "+f"(d[48]), "+f"(d[49]), "+f"(d[50]), "+f"(d[51]), "+f"(d[52]), "+f"(d[53]), "+f"(d[54]), "+f"(d[55]), "+f"(d[56]), "+f"(d[57]), "+f"(d[58]), "+f"(d[59]), "+f"(d[60]), "+f"(d[61]), "+f"(d[62]), "+f"(d[63]), "+f"(d[64]), "+f"(d[65]), "+f"(d[66]), "+f"(d[67]), "+f"(d[68]), "+f"(d[69]), "+f"(d[70]), "+f"(d[71]), "+f"(d[72]), "+f"(d[73]), "+f"(d[74]), "+f"(d[75]), "+f"(d[76]), "+f"(d[77]), "+f"(d[78]), "+f"(d[79]), "+f"(d[80]), "+f"(d[81]), "+f"(d[82]), "+f"(d[83]), "+f"(d[84]), "+f"(d[85]), "+f"(d[86]), "+f"(d[87]), "+f"(d[88]), "+f"(d[89]), "+f"(d[90]), "+f"(d[91]), "+f"(d[92]), "+f"(d[93]), "+f"(d[94]), "+f"(d[95])
    : "l"(descA), "l"(descB), "r"(accum));
}
template <> __device__ __forceinline__ void wgmma_ss<184>(float* d, uint64_t descA, uint64_t descB, uint32_t accum) {
  asm volatile(
    "{\n.reg .pred p;\n"
    "setp.ne.b32 p, %94, 0;\n"
    "wgmma.mma_async.sync.aligned.m64n184k16.f32.bf16.bf16 "
    "{%0, %1, %2, %3, %4, %5, %6, %7, %8, %9, %10, %11, %12, %13, %14, %15, %16, %17, %18, %19, %20, %21, %22, %23, %24, %25, %26, %27, %28, %29, %30, %31, %32, %33, %34, %35, %36, %37, %38, %39, %40, %41, %42, %43, %44, %45, %46, %47, %48, %49, %50, %51, %52, %53, %54, %55, %56, %57, %58, %59, %60, %61, %62, %63, %64, %65, %66, %67, %68, %69, %70, %71, %72, %73, %74, %75, %76, %77, %78, %79, %80, %81, %82, %83, %84, %85, %86, %87, %88, %89, %90, %91}, "
    "%92, %93, p, 1, 1, 0, 0;\n"
    "}\n"
    : "+f"(d[0]), "+f"(d[1]), "+f"(d[2]), "+f"(d[3]), "+f"(d[4]), "+f"(d[5]), "+f"(d[6]), "+f"(d[7]), "+f"(d[8]), "+f"(d[9]), "+f"(d[10]), "+f"(d[11]), "+f"(d[12]), "+f"(d[13]), "+f"(d[14]), "+f"(d[15]), "+f"(d[16]), "+f"(d[17]), "+f"(d[18]), "+f"(d[19]), "+f"(d[20]), "+f"(d[21]), "+f"(d[22]), "+f"(d[23]), "+f"(d[24]), "+f"(d[25]), "+f"(d[26]), "+f"(d[27]), "+f"(d[28]), "+f"(d[29]), "+f"(d[30]), "+f"(d[31]), "+f"(d[32]), "+f"(d[33]), "+f"(d[34]), "+f"(d[35]), "+f"(d[36]), "+f"(d[37]), "+f"(d[38]), "+f"(d[39]), "+f"(d[40]), "+f"(d[41]), "+f"(d[42]), "+f"(d[43]), "+f"(d[44]), "+f"(d[45]), "+f"(d[46]), "+f"(d[47]), "+f"(d[48]), "+f"(d[49]), "+f"(d[50]), "+f"(d[51]), "+f"(d[52]), "+f"(d[53]), "+f"(d[54]), "+f"(d[55]), "+f"(d[56]), "+f"(d[57]), "+f"(d[58]), "+f"(d[59]), "+f"(d[60]), "+f"(d[61]), "+f"(d[62]), "+f"(d[63]), "+f"(d[64]), "+f"(d[65]), "+f"(d[66]), "+f"(d[67]), "+f"(d[68]), "+f"(d[69]), "+f"(d[70]), "+f"(d[71]), "+f"(d[72]), "+f"(d[73]), "+f"(d[74]), "+f"(d[75]), "+f"(d[76]), "+f"(d[77]), "+f"(d[78]), "+f"(d[79]), "+f"(d[80]), "+f"(d[81]), "+f"(d[82]), "+f"(d[83]), "+f"(d[84]), "+f"(d[85]), "+f"(d[86]), "+f"(d[87]), "+f"(d[88]), "+f"(d[89]), "+f"(d[90]), "+f"(d[91])
    : "l"(descA), "l"(descB), "r"(accum));
}

template <int N> struct IC { static constexpr int v = N; };

__device__ __forceinline__ void stmatrix_x4_t(uint32_t addr, uint32_t r0, uint32_t r1, uint32_t r2, uint32_t r3) {
  asm volatile("stmatrix.sync.aligned.m8n8.x4.trans.shared.b16 [%0], {%1, %2, %3, %4};"
               ::"r"(addr), "r"(r0), "r"(r1), "r"(r2), "r"(r3) : "memory");
}
__device__ __forceinline__ void ldmatrix_x4(uint32_t* r, uint32_t addr) {
  asm volatile("ldmatrix.sync.aligned.m8n8.x4.shared.b16 {%0, %1, %2, %3}, [%4];"
               : "=r"(r[0]), "=r"(r[1]), "=r"(r[2]), "=r"(r[3]) : "r"(addr) : "memory");
}
__device__ __forceinline__ void ldmatrix_x4_if(uint32_t* r, uint32_t addr, uint32_t c) {
  asm volatile("{\n.reg .pred p;\nsetp.eq.u32 p, %5, 0;\n@p ldmatrix.sync.aligned.m8n8.x4.shared.b16 {%0, %1, %2, %3}, [%4];\n}\n"
               : "+r"(r[0]), "+r"(r[1]), "+r"(r[2]), "+r"(r[3]) : "r"(addr), "r"(c) : "memory");
}
__device__ __forceinline__ uint32_t pack_bf16(float a, float b) {
  __nv_bfloat162 v = __floats2bfloat162_rn(a, b);
  return *reinterpret_cast<uint32_t*>(&v);
}
__device__ __forceinline__ uint32_t prmt(uint32_t a, uint32_t b, uint32_t s) {
  uint32_t d;
  asm("prmt.b32 %0, %1, %2, %3;" : "=r"(d) : "r"(a), "r"(b), "r"(s));
  return d;
}
__device__ __forceinline__ uint32_t lds32(uint32_t a) {
  uint32_t v;
  asm volatile("ld.shared.u32 %0, [%1];" : "=r"(v) : "r"(a) : "memory");
  return v;
}
__device__ __forceinline__ void lds128(uint32_t* v, uint32_t a) {
  asm volatile("ld.shared.v4.u32 {%0, %1, %2, %3}, [%4];" : "=r"(v[0]), "=r"(v[1]), "=r"(v[2]), "=r"(v[3]) : "r"(a) : "memory");
}
__device__ __forceinline__ void sts128(uint32_t a, const uint32_t* v) {
  asm volatile("st.shared.v4.u32 [%0], {%1, %2, %3, %4};" ::"r"(a), "r"(v[0]), "r"(v[1]), "r"(v[2]), "r"(v[3]) : "memory");
}
__device__ __forceinline__ void sts32(uint32_t a, uint32_t v) {
  asm volatile("st.shared.u32 [%0], %1;" ::"r"(a), "r"(v) : "memory");
}
__device__ __forceinline__ void wait_until(uint32_t t0, uint32_t at) {
  asm volatile(
      "{\n.reg .pred p;\n.reg .s32 r;\n"
      "SPIN:\n"
      "mov.u32 r, %%clock;\n"
      "sub.s32 r, %0, r;\n"
      "setp.gt.s32 p, r, 0;\n"
      "shr.s32 r, r, %1;\n"
      "@p nanosleep.u32 r;\n"
      "@p bra.uni SPIN;\n}\n"
      ::"r"(t0 + at), "n"(NSH) : "memory");
}
__device__ __forceinline__ void spin_until(uint32_t t0, uint32_t at) {
  while ((uint32_t)clock() - t0 < at) {}
}
__device__ __forceinline__ void wait_count(const unsigned int* f, uint32_t& c) {
  asm volatile(
      "{\n.reg .pred p;\n.reg .u32 v;\n"
      "SPIN:\n"
      "ld.acquire.gpu.global.u32 v, [%1];\n"
      "add.u32 %0, %0, 16;\n"
      "setp.lt.u32 p, %0, 0x100000;\n"
      "setp.lt.and.u32 p, v, 64, p;\n"
      "@p nanosleep.u32 100;\n"
      "@p bra.uni SPIN;\n}\n"
      : "+r"(c) : "l"(f) : "memory");
}
template <int E>
__device__ __forceinline__ void ld_lut(uint32_t* v, const __nv_bfloat16* p) {
  asm volatile("ld.global.nc.u32 %0, [%1+%2];" : "=r"(v[E]) : "l"(p), "n"(((E & 3) * N_ + 8 * (E >> 2)) * 2));
  if constexpr (E < 7) ld_lut<E + 1>(v, p);
}
template <int OFF>
__device__ __forceinline__ void ld_codes4(uint32_t* w, const int* p) {
  asm volatile("ld.global.nc.L1::no_allocate.v4.u32 {%0, %1, %2, %3}, [%4+%5];" : "=r"(w[0]), "=r"(w[1]), "=r"(w[2]), "=r"(w[3]) : "l"(p), "n"(OFF));
}
__device__ __forceinline__ void ld_codes(uint32_t* w, const int* p) {
  ld_codes4<0>(w, p);
  ld_codes4<N_ * 4>(w + 4, p);
  ld_codes4<N_ * 32>(w + 8, p);
  ld_codes4<N_ * 36>(w + 12, p);
}
__device__ __forceinline__ void prefetch_map(const CUtensorMap* map) {
  asm volatile("prefetch.tensormap [%0];" ::"l"((uint64_t)map) : "memory");
}
template <int OFF>
__device__ __forceinline__ void ld_words(uint32_t* w, const uint8_t* p) {
  asm volatile("ld.relaxed.gpu.global.v4.u32 {%0, %1, %2, %3}, [%4+%5];" : "=r"(w[0]), "=r"(w[1]), "=r"(w[2]), "=r"(w[3]) : "l"(p), "n"(OFF) : "memory");
}
template <int OFF>
__device__ __forceinline__ void st_words(uint8_t* p, const uint32_t* w) {
  asm volatile("st.relaxed.gpu.global.v4.u32 [%0+%5], {%1, %2, %3, %4};" ::"l"(p), "r"(w[0]), "r"(w[1]), "r"(w[2]), "r"(w[3]), "n"(OFF) : "memory");
}

#define DBGR(i, j)
#define DBG(i)

__device__ __forceinline__ uint32_t word_key(uint32_t odd) { return 0xcdf00000u + (odd << 19); }
__device__ __forceinline__ uint32_t make_word(uint32_t c0, uint32_t c1, uint32_t c2, uint32_t c3, uint32_t key) {
  uint32_t p01, p23, n, w;
  asm("mad.lo.u32 %0, %1, 16, %2;" : "=r"(p01) : "r"(c1), "r"(c0));
  asm("mad.lo.u32 %0, %1, 16, %2;" : "=r"(p23) : "r"(c3), "r"(c2));
  asm("mad.lo.u32 %0, %1, 256, %2;" : "=r"(n) : "r"(p23), "r"(p01));
  asm("mad.lo.u32 %0, %1, 0x7fff, %2;" : "=r"(w) : "r"((n & 0x8888u) | key), "r"(n));
  return w;
}
struct Planes { uint32_t v[4][4]; };
__device__ __forceinline__ void lookup4(const Planes& pl, int c, uint32_t s, uint32_t sc, uint32_t& o0, uint32_t& o1) {
  uint32_t s2;
  asm("{\n.reg .b16 l, h;\n.reg .b32 t;\nmov.b32 {l, h}, %1;\nmov.b32 t, {h, h};\nmul.rn.f16x2 %0, t, %2;\n}\n" : "=r"(s2) : "r"(s), "r"(sc));
  const uint32_t lo = prmt(prmt(pl.v[0][2 * c], pl.v[1][2 * c], s), prmt(pl.v[2][2 * c], pl.v[3][2 * c], s), s2);
  const uint32_t hi = prmt(prmt(pl.v[0][2 * c + 1], pl.v[1][2 * c + 1], s), prmt(pl.v[2][2 * c + 1], pl.v[3][2 * c + 1], s), s2);
  o0 = prmt(lo, hi, 0x5140);
  o1 = prmt(lo, hi, 0x7362);
}
__device__ __forceinline__ void store_planes(uint32_t dst, const uint32_t* lv) {
#pragma unroll
  for (int h = 0; h < 2; h++) {
    uint32_t qp[4];
#pragma unroll
    for (int c = 0; c < 2; c++) {
      const uint32_t a = prmt(lv[4 * c], lv[4 * c + 1], h ? 0x7362 : 0x5140), b = prmt(lv[4 * c + 2], lv[4 * c + 3], h ? 0x7362 : 0x5140);
      qp[2 * c] = prmt(a, b, 0x5410);
      qp[2 * c + 1] = prmt(a, b, 0x7632);
    }
    sts128(dst + 64 * h, qp);
  }
}
__device__ __forceinline__ bool words_ok(const uint32_t* P, uint32_t tag) {
  return (P[0] & P[1] & P[2] & P[3] & P[4] & P[5] & P[6] & P[7] & tag) != 0;
}
template <int NJ>
__device__ __forceinline__ void stage_part(const float* a, uint32_t sts) {
#pragma unroll
  for (int j = 0; j < NJ; j++)
    stmatrix_x4_t(sts + 16 * j * 128, pack_bf16(a[8 * j], a[8 * j + 1]), pack_bf16(a[8 * j + 2], a[8 * j + 3]),
                  pack_bf16(a[8 * j + 4], a[8 * j + 5]), pack_bf16(a[8 * j + 6], a[8 * j + 7]));
}

template <int OFF>
__device__ __forceinline__ uint32_t lut_at(uint32_t tab, uint32_t c) {
  uint32_t v;
  asm volatile("ld.shared.u16 %0, [%1+%2];" : "=r"(v) : "r"(tab + 40 * c), "n"(OFF));
  return v;
}
template <int J>
__device__ __forceinline__ void convert_col(const uint32_t (*v)[4], uint32_t tab, uint8_t* dst) {
  uint32_t o[4];
#pragma unroll
  for (int i = 0; i < 4; i++) {
    const uint32_t a = lut_at<2 * J>(tab, v[2 * i][J]), b = lut_at<2 * J>(tab, v[2 * i + 1][J]);
    asm("mad.lo.u32 %0, %1, 65536, %2;" : "=r"(o[i]) : "r"(b), "r"(a));
  }
  st_words<2048 * J>(dst, o);
}

template <int J>
__device__ __forceinline__ void convert_shfl(const uint32_t (*v)[4], uint32_t e, uint8_t* dst) {
  uint32_t o[4];
#pragma unroll
  for (int i = 0; i < 4; i++) {
    uint32_t a, b;
    asm volatile("shfl.sync.idx.b32 %0, %1, %2, 0x101f, 0xffffffff;" : "=r"(a) : "r"(e), "r"(v[2 * i][J]));
    asm volatile("shfl.sync.idx.b32 %0, %1, %2, 0x101f, 0xffffffff;" : "=r"(b) : "r"(e), "r"(v[2 * i + 1][J]));
    o[i] = prmt(a, b, J & 1 ? 0x7632 : 0x5410);
  }
  st_words<2048 * J>(dst, o);
}

struct Maps { CUtensorMap m[NMAPS]; uint64_t desc[6]; uint32_t tiles[66], jobs[396]; };
struct Tab { uint32_t tiles[66], jobs[396]; };
constexpr int imin(int a, int b) { return a < b ? a : b; }
constexpr Tab make_tab() {
  Tab m{};
  for (int t = 0; t < 66; t++) {
    const int u = t - 32, g = t < 32 ? t & 7 : 1 + u % 7, j = t < 32 ? t >> 3 : 4 + u / 7;
    int cl = t >= 60 ? (int)((0x413B3F394035ull >> (8 * (t - 60))) & 0xff) : g == GB ? 48 + 2 * j : g ? 6 * j + g - 1 - (g > GB) : imin(49 + 6 * j, 87 - 12 * j);
    if (GMAP == 0) cl = (t + 4) % 66;
    const int yi = cl / 6, fb = 2 * (cl % 6);
    const int fa = cl < 48 ? fb : 12 + 2 * (cl & 1), ta = cl < 48 ? TA * yi : imin(TC * ((cl - 48) >> 1), M_ - TC);
    m.tiles[t >= 62 ? t & 3 : t + 4] = fa | fb << 4 | ta << 5 | (TD * yi - (TB - TD) * imin(8 - yi, 0)) << 13;
  }
  int third[396] = {}, t2[396] = {}, by[896] = {}, nt = 0, na = 0;
  for (int i = 0; i < 396; i++) {
    third[i] = (m.tiles[i / 6] & 15) >= 12 && i % 3 < NB3;
    t2[i] = 1;
    nt += third[i];
  }
  for (int i = 0, k = 0; i < 396; i++)
    if (third[i] && i % 3 == NB3 - 1 && (k++) % 3 == 0 && k < 3 * NTB) t2[i] = 0;
  const int need = 104 - nt;
  for (int b = 0, k = 0; b < 132; b++) {
    if ((m.tiles[b / 2] & 15) >= 12) continue;
    if ((na / 2 + 1) * need / 96 != (na / 2) * need / 96) {
      third[3 * b] = 1;
      if (k < 12 - NTB) t2[3 * b] = 0;
      k++;
    }
    na++;
  }
  int u = 920, l = 0;
  for (int pass = 0; pass < 2; pass++)
    for (int i = 0; i < 396; i++) {
      if (BF1 ? ((m.tiles[i / 6] & 15) >= 12) == pass : pass) continue;
      m.jobs[i] = third[i] ? u++ : 1024;
      by[third[i] ? m.jobs[i] - 128 : 396 + U0(i / 3, i % 3)] = i + 1;
    }
  for (int k = 0; k < 896; k++) {
    const int i = by[k] - 1;
    if (i < 0) continue;
    if (t2[i]) m.jobs[i] |= l << 11 | imin(LCAP, LT0 + l * LTS) / 8 << 20, l++;
    else m.jobs[i] |= 384 << 11;
  }
  return m;
}

#define TILES() \
  const int fta = (te & 15) + rank, ftb = ((te >> 4) & 15) + rank, toka = (te >> 5) & 0x7f8, tokb = (te >> 13) & 0x7f8; \
  const bool big = fta < 12; \
  (void)toka; (void)big; (void)tokb; (void)ftb
__global__ void __cluster_dims__(2, 1, 1) __launch_bounds__(NTHREADS, 1)
fused_kernel(unsigned int* __restrict__ count, const __nv_bfloat16* __restrict__ lut, uint8_t* __restrict__ gp,
             const int* __restrict__ qw, const uint8_t* __restrict__ xg, const __grid_constant__ Maps maps) {
  extern __shared__ __align__(1024) uint8_t smem_gen[];
  const uint32_t t0 = clock();
  const int tid = threadIdx.x;
  uint32_t cf[16];
  const int* src = qw + (((tid >> 8) * BK + 32 + (tid & 48) + ((tid >> 1) & 6)) * N_ + (blockIdx.x & 127) * 16 + (tid & 3) * 4);
  uint32_t ep0 = 0;
  if ((tid >> 6) == 2) {
    if (EPW) asm volatile("ld.relaxed.gpu.global.u32 %0, [%1];" : "=r"(ep0) : "l"(count) : "memory");
    ld_codes(cf, src);
  }
  const uint32_t te = maps.tiles[blockIdx.x >> 1];
  const int rank = blockIdx.x & 1;
  const uint32_t sl = SLC ? SB + (rank << 24) : smem_u32(smem_gen);
  auto bar = [&](int i) { return sl + OFF_BAR + 8 * i; };
  const int w12 = __shfl_sync(0xffffffffu, tid >> 5, 0);
  const int wg = w12 >> 2;
  const int warp = w12 & 3;
  const int lane = tid & 31;
  uint32_t bud = 0;
  if (__builtin_expect(wg == 0, 1)) {
    asm volatile("setmaxnreg.dec.sync.aligned.u32 72;");
    if (warp == 0) {
      if (lane == 0) {
#pragma unroll
        for (int i = 0; i < NBARS; i++) mbar_init(bar(i), i >= 4 && i < 8 ? 4 : 1);
        mbar_init(bar(B_LAST), 4);
        mbar_init(bar(B_W), 1);
        asm volatile("fence.mbarrier_init.release.cluster;" ::: "memory");
      }
      __syncwarp();
      cluster_arrive_relaxed();
      asm volatile("bar.arrive 4, 128;" ::: "memory");
      DBG(1);
      TILES();
      expect_w(bar(B_DIR), 2 * UNIT_BYTES);
      tma3_w(sl + 3 * STAGE_BYTES, &maps.m[M_D], bar(B_DIR), 0, 0, fta * 4);
      const int ca = TR1 && !big ? (TA - TC) * 128 : 0, cb = TR2 && big ? (TB - TD) * 128 : 0;
      const CUtensorMap *ma = &maps.m[M_XA + (ca ? rank : 0)], *mb = &maps.m[M_XB + (cb ? rank : 0)];
      expect_w(bar(B_FULL), X_BYTES - ca);
      cluster_wait();
      tma_mc_w(sl + rank * (X_BYTES / 2), ma, bar(B_FULL), 0, toka + rank * (TA / 2));
      DBG(2);
      expect_w(bar(B_LAST), SLAB_BYTES);
      wait_until(t0, XT0);
#define PT(a)
#pragma unroll 1
      for (int n = 1; n < 2 * KBLKS - 4; n++) {
        const int stage = n & 3;
        const bool first = n < KBLKS;
        const int rows = rank * (first ? TA / 2 : TB / 2);
        if (EXF) expect_w(bar(B_FULL + stage), STAGE_BYTES - (first ? ca : cb));
        mbar_wait(bar(B_EMPTY + stage), ((n - 3) >> 2) & 1, bud);
        PT(pe);
        if (!EXF) expect_w(bar(B_FULL + stage), STAGE_BYTES - (first ? ca : cb));
        tma_mc_w(sl + stage * STAGE_BYTES + rows * 128, first ? ma : mb, bar(B_FULL + stage),
                 (n & (KBLKS - 1)) * BK, (first ? toka : tokb) + rows);
        PT(px);
        if (XPD && n >= XPS && n < KBLKS - XPD) {
          const uint8_t* a = xg + (((blockIdx.x & 127) * 16 + (lane >> 1)) * (K_ * 2) + (lane & 1) * 64 + (n + XPD) * 128);
          asm volatile("prefetch.global.L2 [%0];" ::"l"(a));
          if (!XPW) asm volatile("prefetch.global.L2 [%0+32];" ::"l"(a));
        }
        if (n <= KBLKS) {
          wait_until(t0, 32 * prmt((uint32_t)GATES, (uint32_t)(GATES >> 32), min(n, 7)));
          bulk_w(sl + ((n - 1) & 3) * STAGE_BYTES + X_BYTES, gp + (fta * KBLKS + n - 1) * SLAB_BYTES, SLAB_BYTES, bar(B_FULL + (n & 19)));
        }
        if (WP && n == 13) asm volatile("bar.arrive 0, 64;" ::: "memory");
        if (WP) continue;
        if (n == PN) wait_count(count + 32 * (1 + ((lds32(sl + OFF_EPOCH) & 256) ? 48 : 0) + 4 * ftb), bud);
        if (first) continue;
        if (n == KBLKS + 4 || n == KBLKS + 8) asm volatile("bar.sync %0, 64;" ::"r"(n & 8) : "memory");
        tma_w(sl + stage * STAGE_BYTES + TB * 128, &maps.m[W128 ? M_W2 : M_W], bar(B_FULL + stage), (n - KBLKS) * BK, ftb * BF);
        if (!W128) tma_w(sl + stage * STAGE_BYTES + TB * 128 + 8192, &maps.m[M_W], bar(B_FULL + stage), (n - KBLKS) * BK, ftb * BF + 64);
        PT(pw);
      }
      const CUtensorMap *mx = &maps.m[M_XB], *mw = &maps.m[M_W];
      DBG(220);
      expect_w(bar(B_RDY), 16384);
      expect_w(bar(B_W), 16384);
      asm volatile("bar.sync 15, %0;" ::"n"(WP ? 128 : 96) : "memory");
      tma3_w(sl + OFF_STG + 49152, mw, bar(B_W), 0, ftb * BF, 14);
      expect_w(bar(B_FULL), STAGE_BYTES);
      uint32_t xd = sl + rank * 12288, xb = bar(B_FULL), xk = (12 + rank) * BK, xt = tokb, wd = sl + 24576, wb = xb, wf = ftb * BF, wk = 12;
#pragma unroll 1
      for (int i = 0; i < 4; i++) {
        wait_tma_mc_w(bar(B_EMPTY) + 8 * i, i == 3, bud, xd, mx, xb, xk, xt);
        if (i < 2) tma3_w(wd, mw, wb, 0, wf, wk);
        wf = ftb * BF + 64;
        if (i == 0) tma3_w(sl + OFF_STG + 16384, mw, bar(B_RDY), 0, wf, 12);
        if (i < 3) expect_w(bar(B_FULL + 1) + 8 * i, i == 2 ? 49152 - 4 * cb : 24576 - 8192 * i);
        xd += STAGE_BYTES; wd += STAGE_BYTES; xk ^= 2 * BK; wk = 14; wb = bar(B_FULL + 2);
        if (i) xb = bar(B_FULL + 3), xt = tokb + TB / 2, mx = &maps.m[cb ? M_XD : M_XB];
        else xb = bar(B_FULL + 1);
      }
      asm volatile(ELECT "@p red.relaxed.gpu.global.add.u32 [%0], %1;\n}\n" ::"l"(count), "r"(blockIdx.x < 2 * NUM_CTAS - 256 ? 1 : 2) : "memory");
    } else {
      const int p = warp - 1;
      uint32_t ep;
      asm volatile("ld.relaxed.gpu.global.u32 %0, [%1];" : "=r"(ep) : "l"(count) : "memory");
      cluster_arrive_relaxed();
      prefetch_map(&maps.m[p + (TR1 && p == 2 && (te & 15) >= 12 ? rank : 0)]);
      asm volatile("prefetch.global.L2 [%0];" ::"l"(xg + (((blockIdx.x * 16 + p * 8 + (lane >> 2)) & (M_ - 1)) * (K_ * 2) + (lane & 3) * 32)));
      const uint32_t so = OFF_STG + p * UNIT_BYTES;
      const uint32_t ua = sl + so + (lane & 3) * 256 + (((lane >> 2) ^ (2 * (lane & 3))) << 4);
      asm volatile("bar.sync 4, 128;" ::: "memory");
      if (!EPW && p == 2) {
        sts32(sl + OFF_EPOCH, ep);
        asm volatile("bar.arrive 1, 288;" ::: "memory");
      }
      int r = blockIdx.x, u = 128 + U0(r, p);
      const uint32_t job = maps.jobs[3 * r + p];
      uint32_t ph = 0, odd;
#pragma unroll 1
      do {
        wait_until(t0, D0 + (u - 128) * PU / 4);
        expect_w(bar(B_SLOT + p), UNIT_BYTES);
        tma_w(sl + so, &maps.m[M_Q], bar(B_SLOT + p), (u & 63) * 32, (u & ~63) + 32);
        DBG(16 + 8 * p + 2 * (r / NUM_CTAS));
        uint8_t* dst = gp + (((((u & 63) >> 2) * KBLKS + (u >> 6)) * 4 + (u & 3)) * 2048 + (lane >> 2) * 256 + (lane & 3) * 16);
        mbar_wait(bar(B_SLOT + p), ph, bud);
        asm volatile("and.b32 %0, %1, 256;" : "=r"(odd) : "r"(ep));
        DBG(184 + 4 * p + r / NUM_CTAS);
        uint32_t w[4][4];
#pragma unroll
        for (int b = 0; b < 4; b++) {
          uint32_t v[4][4];
          lds128(v[0], ua + b * 2048);
          lds128(v[1], (ua ^ 16) + b * 2048 + 128);
          lds128(v[2], ua + b * 2048 + 1024);
          lds128(v[3], (ua ^ 16) + b * 2048 + 1024 + 128);
#pragma unroll
          for (int j = 0; j < 4; j++) w[j][b] = make_word(v[0][j], v[1][j], v[2][j], v[3][j], word_key(odd));
        }
        st_words<0>(dst, w[0]); st_words<64>(dst, w[1]); st_words<128>(dst, w[2]); st_words<192>(dst, w[3]);
        __syncwarp();
        DBG(17 + 8 * p + 2 * (r / NUM_CTAS));
        ph ^= 1;
        r += NUM_CTAS;
        u = ph ? u + 3 * NUM_CTAS : job & 2047;
      } while (u < 1024);
      const int l = (job >> 11) & 511;
      const int ls = (l * 1366) >> 16, cg = l - 48 * ls;
      unsigned int* cnt = count + (32 + 6 * __shfl_sync(0xffffffffu, odd, 0));
      prefetch_map(&maps.m[M_XB + p]);
      prefetch_map(&maps.m[M_Q2]);
      if (l < 384) {
        uint32_t e[8];
        const __nv_bfloat16* s = lut + ((lane & 15) * N_ + 2048 + cg * 32 + (lane & 16));
        asm volatile("ld.global.nc.v4.u32 {%0, %1, %2, %3}, [%4];" : "=r"(e[0]), "=r"(e[1]), "=r"(e[2]), "=r"(e[3]) : "l"(s));
        asm volatile("ld.global.nc.v4.u32 {%0, %1, %2, %3}, [%4+16];" : "=r"(e[4]), "=r"(e[5]), "=r"(e[6]), "=r"(e[7]) : "l"(s));
        wait_until(t0, (job >> 20) * 8);
        expect_w(bar(B_SLOT + p), 2 * UNIT_BYTES);
        tma3_w(sl + so, &maps.m[M_Q2], bar(B_SLOT + p), 2048 + cg * 32, ls * 16, 0);
        tma3_w(sl + so + 32768, &maps.m[M_Q2], bar(B_SLOT + p), 2048 + cg * 32, ls * 16, 4);
        DBG(22 + 8 * p);
        uint32_t tab = sl + OFF_TAB + p * 1536 + (SHF ? lane * 32 : (lane >> 4) * 644);
        if (SHF) {
          sts128(tab, e);
          sts128(tab + 16, e + 4);
        } else {
#pragma unroll
          for (int i = 0; i < 8; i++) sts32(tab + (lane & 15) * 40 + 4 * i, e[i]);
          __syncwarp();
        }
        uint8_t* dst = gp + (W_OFF + cg * 65536 + ls * 256 + (lane >> 4) * 32768 + (lane & 15) * 16);
        const uint32_t src = sl + so + (lane & 15) * 128 + ((((lane >> 2) & 4) ^ (lane & 7)) << 4);
        mbar_wait(bar(B_SLOT + p), ph, bud);
#pragma unroll 1
        for (int c = 0; c < 64; c += 16, tab += 8, dst += 8192) {
          uint32_t v[8][4];
#pragma unroll
          for (int i = 0; i < 8; i++) lds128(v[i], (src ^ c) + (i & 3) * 2048 + (i >> 2) * 32768);
          if (SHF) {
            asm volatile("ld.shared.v2.u32 {%0, %1}, [%2];" : "=r"(e[0]), "=r"(e[1]) : "r"(tab) : "memory");
            convert_shfl<0>(v, e[0], dst);
            convert_shfl<1>(v, e[0], dst);
            convert_shfl<2>(v, e[1], dst);
            convert_shfl<3>(v, e[1], dst);
          } else {
          convert_col<0>(v, tab, dst);
          convert_col<1>(v, tab, dst);
          convert_col<2>(v, tab, dst);
          convert_col<3>(v, tab, dst);
          }
        }
        __syncwarp();
        DBG(23 + 8 * p);
      }
      arrive_w(bar(B_LAST));
      if (l < 384)
        asm volatile(ELECT "@p fence.proxy.async.global;\n@p red.release.gpu.global.add.u32 [%0], %1;\n}\n"
                     ::"l"(cnt + 32 * ((cg & ~3) + min(ls >> 1, 2))), "r"(ls < 4 ? 8 : 4) : "memory");
      cluster_wait();
      TILES();
      const int q = WP ? (RM >> (p + p)) & 3 : p;
      prefetch_map(&maps.m[M_W - q]);
      prefetch_map(&maps.m[M_W2]);
      if (q > 0) {
        asm volatile("bar.sync %0, 160;" ::"r"(12 + q) : "memory");
        if (FEN) asm volatile("fence.proxy.async.shared::cta;" ::: "memory");
        uint32_t t1 = clock();
#pragma unroll 1
        for (int i = 0; i < TA; i += OB, t1 += PC * OB / 32) {
          wait_until(t1, 0);
          const int rr = min(i ^ 128, (big ? TA : TC) - OB);
          if (i == 128) {
            bulk_wait_read();
            asm volatile("bar.arrive 15, %0;" ::"n"(WP ? 128 : 96) : "memory");
          }
          store_w(&maps.m[M_O32], sl + OFF_STG + (q - 1) * 32768 + rr * 128, fta * BF + 64 * (q - 1), toka + rr);
        }
        bulk_wait_read();
        DBG(227 + q);
        asm volatile("bar.arrive %0, 160;" ::"r"(12 + q) : "memory");
        const uint32_t sg = sl + OFF_STG + (q - 1) * 32768;
        const int c0 = 2048 + ftb * BF + 64 * (q - 1);
        uint32_t ids = q == 1 ? 0x0d126 : 0x8e437;
        const CUtensorMap* mo = &maps.m[M_O48];
        uint32_t os = sg + 48 * 128, ot = tokb + 48;
#pragma unroll 1
        for (int k = 0; k < 5; k++) {
          asm volatile("bar.sync %0, 160;\nfence.proxy.async.shared::cta;\n"
                       ELECT "@p cp.async.bulk.tensor.2d.global.shared::cta.bulk_group [%1, {%3, %4}], [%2];\n}\n"
                       "cp.async.bulk.commit_group;"
                       ::"r"((ids & 15) | ((os + ot + k + (uint32_t)((uint64_t)mo >> 32)) & (bud >> 31))), "l"((uint64_t)mo), "r"(os), "r"(c0), "r"(ot) : "memory");
          const int r = k ? 64 + 32 * k : 0;
          ids >>= 4; os = sg + r * 128; ot = tokb + r;
          if (k == 1 || (k == 3 && big)) mo--;
        }
        bulk_wait_read();
      } else {
        if (blockIdx.x < 48) count[32 * (50 + blockIdx.x) - (cnt - count)] = 0;
        if (WP) {
          asm volatile("bar.sync 0, 64;" ::: "memory");
#pragma unroll 1
          for (int n = 0; n < KBLKS - 4; n++) {
            if ((n & 3) == 0) wait_count(cnt + 32 * 4 * ftb + 8 * n, bud);
            if (n == 8) asm volatile("bar.arrive 15, 128;" ::: "memory");
            mbar_wait(bar(B_EMPTY + (n & 3)), ((n + 13) >> 2) & 1, bud);
            tma_w(sl + (n & 3) * STAGE_BYTES + TB * 128, &maps.m[W128 ? M_W2 : M_W], bar(B_FULL + (n & 3)), n * BK, ftb * BF);
            if (!W128) tma_w(sl + (n & 3) * STAGE_BYTES + TB * 128 + 8192, &maps.m[M_W], bar(B_FULL + (n & 3)), n * BK, ftb * BF + 64);
          }
        } else {
#pragma unroll 1
        for (int i = 1; i < 3; i++) {
          wait_count(cnt + 32 * (4 * ftb + i), bud);
          asm volatile("bar.arrive %0, 64;" ::"r"(8 * i - 8) : "memory");
        }
        }
      }
    }
    asm volatile("exit;");
  }
  const int cw = wg - 1;
  TILES();
  cluster_arrive_relaxed();
  if (warp >= 2) {
    ld_lut<0>(cf, lut + (fta * BF + 4 * (lane & 3) * N_ + 64 * cw + 32 * (warp & 1) + (lane & 16) + ((lane >> 1) & 6)));
  } else if (cw) {
    spin_until(t0, S1D);
    ld_codes(cf, src);
  } else if (EPW) {
    sts32(sl + OFF_EPOCH, ep0);
    asm volatile("bar.arrive 1, 256;" ::: "memory");
  }
  if (EPW) {
    if (w12 >= 6) asm volatile("bar.sync 1, 256;" ::: "memory");
  } else asm volatile("bar.sync 1, 288;" ::: "memory");
  const uint32_t odd = lds32(sl + OFF_EPOCH) & 256;
  DBG(40 + w12);
  if (warp >= 2) store_planes(sl + OFF_PL + cw * 32768 + (warp & 1) * 1024 + (lane & 28) * 32 + (lane & 3) * 16, cf);
  else {
    uint8_t* dst = gp + (((blockIdx.x & 120) * 2 + cw) * SLAB_BYTES + (blockIdx.x & 7) * 1024 + (tid & 63) * 16);
    const uint32_t tb = sl + OFF_STG + 61440 + cw * 1024;
#pragma unroll
    for (int j = 0; j < 4; j++)
      sts32(tb + (lane & 3) * 256 + j * 64 + (lane & 12) * 4 + ((tid >> 2) & 12), make_word(cf[j], cf[4 + j], cf[8 + j], cf[12 + j], word_key(odd)));
    asm volatile("bar.sync %0, 64;" ::"r"(6 + cw) : "memory");
    lds128(cf, tb + (tid & 63) * 16);
    st_words<0>(dst, cf);
  }
  DBG(52 + w12);
  asm volatile("setmaxnreg.inc.sync.aligned.u32 216;");
  uint32_t rel = (tid & 127) < 2 ? mapa(bar(B_EMPTY), lane) : 0u;
  uint32_t tg = (w12 - 4) * 1024 + lane * 16;
  uint32_t tw = sl + X_BYTES + tg;
  const uint8_t* gt = gp + (tg + fta * KBLKS * SLAB_BYTES);
  uint32_t tag = (1u << 28) - (odd << 19), sc = 0x3c00 + 8 * odd;
  asm volatile("" : "+r"(tw), "+l"(gt), "+r"(rel), "+r"(tag), "+r"(sc));
  Planes pl;
  uint32_t A[16], P[8];
  float acc[TA / 2];
  DBG(64 + cw);
  if (PLF) {
  asm volatile("bar.sync %0, 128;" ::"r"(2 + cw) : "memory");
#pragma unroll
  for (int k = 0; k < 4; k++) lds128(pl.v[k], sl + OFF_PL + cw * 32768 + (tid & 124) * 16 + 16 * k);
  }
  {
    const uint32_t td = sl + 3 * STAGE_BYTES - 8192 + (w12 >> 1) * 4096 + (lane & 3) * 256 + ((((tid >> 3) & 4) ^ (lane >> 4) ^ (2 * (lane & 3))) << 4) + (lane & 12);
    mbar_wait(bar(B_DIR), 0, bud);
    DBG(88 + cw);
#pragma unroll
    for (int k = 0; k < 4; k++) {
      const uint32_t a = (td ^ ((k & 2) << 4)) + (k & 1) * 2048;
      P[2 + (k & 1) + 2 * (k & 2)] = make_word(lds32(a), lds32((a ^ 16) + 128), lds32(a + 1024), lds32((a ^ 16) + 1152), word_key(odd));
    }
  }
  if (!PLF) {
  asm volatile("bar.sync %0, 128;" ::"r"(2 + cw) : "memory");
#pragma unroll
  for (int k = 0; k < 4; k++) lds128(pl.v[k], sl + OFF_PL + cw * 32768 + (tid & 124) * 16 + 16 * k);
  }
  mbar_wait(bar(B_FULL), 0, bud);
  DBG(66 + cw);
#define CNT(i)
  auto rest = [&](auto ty) {
  constexpr bool big = decltype(ty)::v;
  auto tile1 = [&](auto nh) {
    uint32_t d = UD, dn, fb = bar(B_FULL + 1), pa = 0;
#pragma unroll 1
    for (int n = 0; n < KBLKS; n++) {
      bool ok;
#pragma unroll
      for (int b = 0; b < 4; b++) {
        const int m = n + 1;
        if (b == WB && !EP1) mbar_wait_fast(fb, (m >> 2) & 1, bud);
        if (b == WB && EP1 == 1 && !ok) mbar_wait(fb, (m >> 2) & 1, bud);
        if (b == 1 && EP1 == 3) ok = mbar_test(fb, (m >> 2) & 1);
        if (b == 1 && EP1 == 5) ok = mbar_peek(fb, (m >> 2) & 1);
        if (b == 2 && EP1 >= 4 && __builtin_expect(!ok, 0)) {
          mbar_wait(fb, (m >> 2) & 1, bud);
          lds128(P, tw + pa);
          lds128(P + 4, tw + pa + 512);
        }
        if (b == 2) {
#pragma unroll 1
          while (__builtin_expect(!words_ok(P, tag), 0)) {
            if ((bud += 16) >= 0x100000) break;
            asm volatile("{\n.reg .u64 a;\nmad.wide.u32 a, %8, 8192, %9;\nld.relaxed.gpu.global.v4.u32 {%0, %1, %2, %3}, [a];\n"
                         "ld.relaxed.gpu.global.v4.u32 {%4, %5, %6, %7}, [a+512];\n}\n"
                         : "=r"(P[0]), "=r"(P[1]), "=r"(P[2]), "=r"(P[3]), "=r"(P[4]), "=r"(P[5]), "=r"(P[6]), "=r"(P[7]) : "r"(n), "l"(gt) : "memory");
          }
          __syncwarp();
        }
        CNT(2 * b);
        lookup4(pl, 0, P[b ^ 2], sc, A[4 * b], A[4 * b + 2]);
        lookup4(pl, 1, P[4 + (b ^ 2)], sc, A[4 * b + 1], A[4 * b + 3]);
        if (b == 1) {
          if ((EP1 == 2 || EP1 == 3) && !ok) mbar_wait(fb, (m >> 2) & 1, bud);
          lds128(P, tw + pa);
          lds128(P + 4, tw + pa + 512);
        }
        if (b == 3) {
          asm volatile("mad.lo.u32 %0, %1, %3, %2;" : "=r"(dn) : "r"(m & 3), "r"(UD), "n"(STAGE_BYTES / 16));
          asm volatile("mad.lo.u32 %0, %1, 8, %2;" : "=r"(fb) : "r"((m + 1) & 19), "r"(bar(B_FULL)));
          asm volatile("mul.lo.u32 %0, %1, %2;" : "=r"(pa) : "r"(m & 3), "n"(STAGE_BYTES));
        }
        if (((WD >> (4 * b)) & 3) == 1) wgmma_wait<1>();
        if (((WD >> (4 * b)) & 3) == 2) wgmma_wait<2>();
        if (b == RB) mbar_arrive_remote_if(rel + 8 * ((n - 1) & 3), rel);
        if (b == S1B && n == S1N && cw == 1) asm volatile("bar.sync 9, 256;" ::: "memory");
        if (b == 0 && (EP1 == 1 || EP1 == 2)) ok = mbar_test(fb, (m >> 2) & 1);
        if (b == 0 && EP1 == 4) ok = mbar_peek(fb, (m >> 2) & 1);
        CNT(2 * b + 1);
        wgmma_fence();
        wgmma_rs<decltype(nh)::v>(acc, A + 4 * b, d + 2 * b, b > 0 || n != 0);
        wgmma_commit();
      }
      d = dn;
    }
  };
  tile1(IC<big ? TA : TC>());
  if (cw != 1) asm volatile("bar.arrive 9, 256;" ::: "memory");
  const uint32_t stg = sl + OFF_STG + cw * 32768;
  const uint32_t so8 = stg + ((lane & 7) + ((lane >> 4) << 3)) * 128 + (((2 * warp + ((lane >> 3) & 1)) ^ (lane & 7)) << 4);
  DBG(212 + cw);
  mbar_wait(bar(B_FULL), 0, bud);
  DBG(214 + cw);
  DBG(216 + cw);
  const uint64_t ub = maps.desc[3 * big], ua = ub + (TB * 8 + cw * 512);
  const uint64_t vb = maps.desc[3 * big + 1], va = vb + (TB * 8 + cw * 512), uc = maps.desc[3 * big + 2];
  wgmma_wait<0>();
  mbar_arrive_remote_if(rel + 24, rel);
  fence_regs(acc);
  DBGR(0, 68 + cw);
#define PKT(i)
  auto start2 = [&](auto nt) {
    uint32_t o[64];
#pragma unroll
    for (int k = 0; k < 48; k++) o[k] = pack_bf16(acc[2 * k], acc[2 * k + 1]);
#pragma unroll
    for (int k = 0; k < 48; k++) asm volatile("" : "+r"(o[k]) :: "memory");
    DBG(92 + cw);
    PKT(0);
    wgmma_fence();
#pragma unroll
    for (int b = 0; b < 4 * NP; b++) {
      const int so = (b >> 2) * (STAGE_BYTES / 16) + 2 * (b & 3);
      if (b && !(b & 3)) mbar_wait(bar(B_FULL + (b >> 2)), 0, bud);
      wgmma_ss<decltype(nt)::v>(acc, ua + so, ub + so, b != 0);
      if ((b & 3) == 3 || (b && !(b & 3))) wgmma_commit();
      if (b == 0) {
#pragma unroll
        for (int k = 48; k < 64; k++) o[k] = pack_bf16(acc[2 * k], acc[2 * k + 1]);
      }
      if (b && !(b & 3)) {
        wgmma_wait<1>();
        mbar_arrive_remote_if(rel + 2 * b - 8, rel);
      }
#pragma unroll
      for (int j = 0; j < 16; j++)
        if (((SMK >> (4 * j)) & 15) == b) stmatrix_x4_t(so8 + (j ^ SJ) * 2048, o[4 * (j ^ SJ)], o[4 * (j ^ SJ) + 1], o[4 * (j ^ SJ) + 2], o[4 * (j ^ SJ) + 3]);
      PKT(b + 1);
    }
  };
  start2(IC<big ? TD : TB>());
  if (!FEN) asm volatile("fence.proxy.async.shared::cta;" ::: "memory");
  asm volatile("bar.arrive %0, 160;" ::"r"(13 + cw) : "memory");
  cluster_wait();
  DBG(70 + cw);
  uint32_t W[64];
  const uint32_t wa = sl + (warp * 16 + (lane & 15)) * 128 + (((lane >> 4) ^ (lane & 7)) << 4);
  const uint32_t w0 = wa + (cw ? OFF_STG + 16384 : 24576), w2 = wa + (cw ? STAGE_BYTES + 24576 : OFF_STG + 49152);
  auto tile2 = [&](auto nt) {
    auto step = [&](int n, bool last) {
      const uint32_t so = (n & 3) * (STAGE_BYTES / 16);
      mbar_wait_fast(bar(B_FULL) + 8 * (n & 3), (n >> 2) & 1, bud);
      if (last && EW == 0) mbar_wait(bar(B_W), 0, bud);
      wgmma_fence();
      wgmma_ss<decltype(nt)::v>(acc, va + so, vb + so, 1);
      wgmma_commit();
      if (last) {
        if (EW == 1) mbar_wait(bar(B_W), 0, bud);
#pragma unroll
        for (int b = 8; b < U0A; b++) {
          if (PEEL) ldmatrix_x4_if(W + 4 * b, (w2 ^ ((b & 3) << 5)) + ((b >> 2) & 1) * 8192, cw);
          else ldmatrix_x4(W + 4 * b, (w2 ^ ((b & 3) << 5)) + ((b >> 2) & 1) * 8192);
        }
      }
      wgmma_wait<1>();
      mbar_arrive_remote_if(rel + 8 * ((n - 1) & 3), rel);
#pragma unroll
      for (int b = 1; b < 4; b++) wgmma_ss<decltype(nt)::v>(acc, va + so + 2 * b, vb + so + 2 * b, 1);
      wgmma_commit();
    };
#pragma unroll 1
    for (int n = NP; n < KBLKS - 4; n++) step(n, n == KBLKS - 5 + 8 * cw);
  };
  tile2(IC<big ? TD : TB>());
  float c2[TB / 2];
  DBGR(1, 72 + cw);
  auto ldw = [&](int b) { ldmatrix_x4(W + 4 * b, ((b & 8 ? w2 : w0) ^ ((b & 3) << 5)) + ((b >> 2) & 1) * 8192); };
  const uint32_t b2 = bar(B_FULL + 1 + cw);
  mbar_wait(bar(cw ? B_RDY : B_FULL), 1, bud);
  if (cw) DBG(226);
#pragma unroll
  for (int b = 0; b < PF; b++) {
    ldw(b);
  }
  bool ok = false;
  wgmma_wait<0>();
  mbar_arrive_remote_if(rel + 24, rel);
  if (PKI == -2) ok = mbar_test(b2, 1);
  if (cw) {
    mbar_wait(b2, 1, bud);
    DBG(227);
#pragma unroll
    for (int b = 8; b < UA; b++) ldw(b);
  }
#pragma unroll
  for (int k = 0; k < TB / 2; k++) asm volatile("mov.b32 %0, %1;" : "=f"(c2[k]) : "f"(acc[k]) : "memory");
#pragma unroll
  for (int h = 0; h < 2 - T3; h++) {
    constexpr int L = 48;
    if (h) mbar_wait(bar(B_FULL + 3), 1, bud);
    if (h || cw) asm volatile("bar.sync %0, 256;" ::"r"(9 + 2 * h + cw) : "memory");
    DBGR(2 + 3 * h, 74 + 6 * h + cw);
    if (h == 0 && PKI == -1) ok = mbar_test(b2, 1);
    auto part = [&](auto nn) {
#pragma unroll
      for (int i = 0; i < 16; i++) {
        if (h ? i >= QD1 && i <= QN1 : i >= QD0 && i <= QN0) {
          if (h) wgmma_wait<QD1 - 1>(); else wgmma_wait<QD0 - 1>();
        }
        if (i == 0 || (h == 0 && ((FM0 >> i) & 1))) wgmma_fence();
        const int off = ((2 * h + (i >> 3)) * STAGE_BYTES + ((i >> 2) & 1) * 12288 + L * 128) / 16 + 2 * (i & 3);
        if constexpr (decltype(nn)::v == TB / 2 - L) wgmma_rl<decltype(nn)::v>(c2 + 48 * h + L / 2, W + 4 * i, uc + off);
        else wgmma_rs<decltype(nn)::v>(c2 + 48 * h + L / 2, W + 4 * i, UD + off, 1);
        if (h == 0 && i < IX) wgmma_rl<L>(c2, W + 4 * i, uc + off - L * 8);
        if (i < (h ? QN1 : QN0) || (!h && i == NA)) wgmma_commit();
        if (h == 0) {
          constexpr int J0 = U0A < UA ? U0A : UA;
#pragma unroll
          for (int e = 0; e < LPS; e++) {
            const int j = (i - LD0) * LPS + J0 + e;
            if (j >= J0 && j < UA) ldmatrix_x4_if(W + 4 * j, (w2 ^ ((j & 3) << 5)) + ((j >> 2) & 1) * 8192, cw);
            else if (j >= J0 && j < U0A) ldmatrix_x4_if(W + 4 * j, (w2 ^ ((j & 3) << 5)) + ((j >> 2) & 1) * 8192, cw ^ 1);
            else if (j >= J0 && j < 16) ldw(j);
          }
          if (i == PKI) ok = mbar_test(b2, 1);
          if (i == WI && !ok) mbar_wait(b2, 1, bud);
        }
      }
      wgmma_commit();
    };
    if (h && big) part(IC<TD - TB / 2 - L>()); else part(IC<TB / 2 - L>());
    const int k0 = h ? K0 : K00 + IX;
    if (h) wgmma_fence();
#pragma unroll
    for (int i = h ? 0 : IX; i < 16; i++) {
      const int off = ((2 * h + (i >> 3)) * STAGE_BYTES + ((i >> 2) & 1) * 12288) / 16 + 2 * (i & 3);
      wgmma_rl<L>(c2 + 48 * h, W + 4 * i, uc + off);
      if (i == k0 - 1) {
        wgmma_commit();
        if (!h) asm volatile("bar.sync %0, 160;" ::"r"(13 + cw) : "memory");
        if (!h) {
          wgmma_wait<2>();
          asm volatile("bar.arrive %0, 256;" ::"r"(10 + cw) : "memory");
        }
        wgmma_wait<1>();
#pragma unroll
        for (int k = L / 2; k < 48; k++) asm volatile("" : "+f"(c2[48 * h + k]) :: "memory");
        if (h == TCH) DBGR(8, 218 + cw);
      }
      const int j = i - k0 + 1 + L / 16;
      if (i >= k0 - 1 && j < 6) stage_part<1>(c2 + 48 * h + 8 * j, so8 + 16 * 128 * (6 * h + j));
      if (j == 5) asm volatile("bar.arrive %0, 160;" ::"r"(h ? 1 + 3 * cw : 6 + cw) : "memory");
    }
    wgmma_commit();
    if (h) asm volatile("{\n.reg .pred p;\nsetp.eq.u32 p, %0, 0;\n@p bar.arrive 12, 256;\n}\n" ::"r"(cw) : "memory");
    if (h == TCH) DBGR(9, 230 + cw);
    wgmma_wait<0>();
#pragma unroll
    for (int k = 0; k < L / 2; k++) asm volatile("" : "+f"(c2[48 * h + k]) :: "memory");
    DBGR(3 + 3 * h, 76 + 6 * h + cw);
    stage_part<L / 16>(c2 + 48 * h, so8 + 96 * 128 * h);
    asm volatile("bar.arrive %0, 160;" ::"r"(h ? 8 * cw : 2 + cw) : "memory");
    DBGR(4 + 3 * h, 78 + 6 * h + cw);
  }
  if (T3) {
    mbar_wait(bar(B_FULL + 3), 1, bud);
    asm volatile("bar.sync %0, 256;" ::"r"(11 + cw) : "memory");
    DBGR(5, 80 + cw);
    auto part = [&](auto nn, auto pp) {
      constexpr int p = decltype(pp)::v;
      constexpr int kk = p == 2 ? K4 : K3;
      float* c = c2 + 48 + 16 * p;
      wgmma_fence();
#pragma unroll
      for (int i = 0; i < 16; i++) {
        if (p == 0 && i >= QD3 && i <= QN3) wgmma_wait<QD3 - 1>();
        const int off = ((2 + (i >> 3)) * STAGE_BYTES + ((i >> 2) & 1) * 12288 + 32 * p * 128) / 16 + 2 * (i & 3);
        if constexpr (p == 2 && decltype(nn)::v == R24) wgmma_rs<decltype(nn)::v>(c, W + 4 * i, UD + off, 1);
        else wgmma_rl<decltype(nn)::v>(c, W + 4 * i, uc + off);
        if (p == 0 && i < QN3) wgmma_commit();
        if (p == 2 && i == HI) asm volatile("{\n.reg .pred p;\nsetp.eq.u32 p, %0, 0;\n@p bar.arrive 12, 256;\n}\n" ::"r"(cw) : "memory");
        if (p && i == kk - 1) {
          wgmma_commit();
          wgmma_wait<1>();
#pragma unroll
          for (int k = -16; k < 0; k++) asm volatile("" : "+f"(c[k]) :: "memory");
          if (TCH && p == TCH) DBGR(8, 218 + cw);
        }
        const int j = i - kk + 1;
        if (p && (j == 0 || j == 1)) stage_part<1>(c - 16 + 8 * j, so8 + (64 + 32 * p + 16 * j) * 128);
        if (p && j == 1 + AD) asm volatile("bar.arrive %0, 160;" ::"r"(p == 1 ? 1 + 3 * cw : 13 + cw) : "memory");
      }
      wgmma_commit();
    };
    part(IC<32>(), IC<0>());
    part(IC<32>(), IC<1>());
    part(IC<big ? 24 : 32>(), IC<2>());
    if (HI == 16) asm volatile("{\n.reg .pred p;\nsetp.eq.u32 p, %0, 0;\n@p bar.arrive 12, 256;\n}\n" ::"r"(cw) : "memory");
    if (TCH) DBGR(9, 230 + cw);
    wgmma_wait<0>();
#pragma unroll
    for (int k = 80; k < 96; k++) asm volatile("" : "+f"(c2[k]) :: "memory");
    DBGR(6, 82 + cw);
    stage_part<2>(c2 + 80, so8 + 160 * 128);
    asm volatile("bar.arrive %0, 160;" ::"r"(8 * cw) : "memory");
    DBGR(7, 84 + cw);
  }
  if (big && PADN) {
    asm volatile("{\n.reg .pred p;\nsetp.ge.s32 p, %0, 0;\n@p exit;\n}\n" ::"r"(bud) : "memory");
#pragma unroll
    for (int i = 0; i < PADN; i++) asm volatile("membar.cta;" ::: "memory");
  }
  };
  if (!big) rest(IC<0>()); else rest(IC<1>());
}

typedef CUresult (*EncodeFn)(CUtensorMap*, CUtensorMapDataType, cuuint32_t, void*, const cuuint64_t*, const cuuint64_t*,
                             const cuuint32_t*, const cuuint32_t*, CUtensorMapInterleave, CUtensorMapSwizzle,
                             CUtensorMapL2promotion, CUtensorMapFloatOOBfill);

}

extern "C" void kernel_launch(void* const* d_in, const int* in_sizes, int n_in, void* d_out, int out_size) {
  const __nv_bfloat16* x = (const __nv_bfloat16*)d_in[0];
  const int* qw = (const int*)d_in[1];
  const __nv_bfloat16* lut = (const __nv_bfloat16*)d_in[2];

  static EncodeFn enc = nullptr;
  static unsigned int* count = nullptr;
  static uint8_t* gp = nullptr;
  if (!enc) {
    cudaDriverEntryPointQueryResult q;
    void* fn = nullptr;
    cudaGetDriverEntryPoint("cuTensorMapEncodeTiled", &fn, cudaEnableDefault, &q);
    enc = (EncodeFn)fn;
    cudaGetSymbolAddress((void**)&count, g_count);
    cudaGetSymbolAddress((void**)&gp, g_p);
    cudaFuncSetAttribute(fused_kernel, cudaFuncAttributeMaxDynamicSharedMemorySize, SMEM_BYTES);
  }
  Maps maps;
  const cuuint32_t es[3] = {1, 1, 1};
  auto map2 = [&](int i, CUtensorMapDataType t, const void* p, int d0, int d1, int bytes, int b0, int b1, CUtensorMapL2promotion pr) {
    cuuint64_t dims[2] = {(cuuint64_t)d0, (cuuint64_t)d1};
    cuuint64_t strides[1] = {(cuuint64_t)d0 * bytes};
    cuuint32_t box[2] = {(cuuint32_t)b0, (cuuint32_t)b1};
    enc(&maps.m[i], t, 2, (void*)p, dims, strides, box, es, CU_TENSOR_MAP_INTERLEAVE_NONE, CU_TENSOR_MAP_SWIZZLE_128B, pr, CU_TENSOR_MAP_FLOAT_OOB_FILL_NONE);
  };
  map2(M_XA, CU_TENSOR_MAP_DATA_TYPE_BFLOAT16, x, K_, M_, 2, BK, TA / 2, XPROM);
  map2(M_XC, CU_TENSOR_MAP_DATA_TYPE_BFLOAT16, x, K_, M_, 2, BK, TC - TA / 2, XPROM);
  map2(M_XD, CU_TENSOR_MAP_DATA_TYPE_BFLOAT16, x, K_, M_, 2, BK, TD - TB / 2, XPROM);
  map2(M_XB, CU_TENSOR_MAP_DATA_TYPE_BFLOAT16, x, K_, M_, 2, BK, TB / 2, XPROM);
  map2(M_O24, CU_TENSOR_MAP_DATA_TYPE_BFLOAT16, d_out, N_, M_, 2, 64, 24, CU_TENSOR_MAP_L2_PROMOTION_NONE);
  map2(M_O32, CU_TENSOR_MAP_DATA_TYPE_BFLOAT16, d_out, N_, M_, 2, 64, OB, CU_TENSOR_MAP_L2_PROMOTION_NONE);
  map2(M_O48, CU_TENSOR_MAP_DATA_TYPE_BFLOAT16, d_out, N_, M_, 2, 64, 48, CU_TENSOR_MAP_L2_PROMOTION_NONE);
  map2(M_Q, CU_TENSOR_MAP_DATA_TYPE_INT32, qw, N_, K_, 4, 32, BK, QPROM);
  {
    cuuint64_t dims[3] = {BK, (cuuint64_t)N_ - 2048, KBLKS};
    cuuint64_t strides[2] = {(cuuint64_t)K_ * 2, BK * 2};
    cuuint32_t box[3] = {BK, 64, 2};
    enc(&maps.m[M_W], CU_TENSOR_MAP_DATA_TYPE_BFLOAT16, 3, (void*)(gp + W_OFF), dims, strides, box, es, CU_TENSOR_MAP_INTERLEAVE_NONE,
        CU_TENSOR_MAP_SWIZZLE_128B, XPROM, CU_TENSOR_MAP_FLOAT_OOB_FILL_NONE);
  }
  map2(M_W2, CU_TENSOR_MAP_DATA_TYPE_BFLOAT16, gp + W_OFF, K_, N_ - 2048, 2, BK, 128, XPROM);
  {
    cuuint64_t dims[3] = {(cuuint64_t)N_, (cuuint64_t)K_ / 8, 8};
    cuuint64_t strides[2] = {(cuuint64_t)N_ * 32, (cuuint64_t)N_ * 4};
    cuuint32_t box[3] = {32, 16, 4};
    enc(&maps.m[M_Q2], CU_TENSOR_MAP_DATA_TYPE_INT32, 3, (void*)qw, dims, strides, box, es, CU_TENSOR_MAP_INTERLEAVE_NONE,
        CU_TENSOR_MAP_SWIZZLE_128B, QPROM, CU_TENSOR_MAP_FLOAT_OOB_FILL_NONE);
  }
  {
    cuuint64_t dims[3] = {32, (cuuint64_t)K_, (cuuint64_t)N_ / 32};
    cuuint64_t strides[2] = {(cuuint64_t)N_ * 4, 128};
    cuuint32_t box[3] = {32, 32, 4};
    enc(&maps.m[M_D], CU_TENSOR_MAP_DATA_TYPE_INT32, 3, (void*)qw, dims, strides, box, es, CU_TENSOR_MAP_INTERLEAVE_NONE,
        CU_TENSOR_MAP_SWIZZLE_128B, QPROM, CU_TENSOR_MAP_FLOAT_OOB_FILL_NONE);
  }
  for (int i = 0; i < 6; i++) maps.desc[i] = (0x40000040ull << 32) + UD;
  constexpr Tab tab = make_tab();
  for (int t = 0; t < 66; t++) maps.tiles[t] = tab.tiles[t];
  for (int i = 0; i < 396; i++) maps.jobs[i] = tab.jobs[i];
  fused_kernel<<<NUM_CTAS, NTHREADS, SMEM_BYTES, cudaStreamPerThread>>>(count, lut, gp, qw, (const uint8_t*)x, maps);
}
```

```cpp
#include <cuda_runtime.h>
#include <cuda_bf16.h>
#include <cuda.h>
#include <stdint.h>
#include <cstdio>
#include <algorithm>

namespace {

constexpr int M_ = 2048, K_ = 1024, N_ = 3584;
constexpr int BF = 128, BK = 64;
constexpr int TA = 256, TB = 192;
#define TCC 232
constexpr int TC = TCC, TD = 184;
constexpr int STAGES = 4;
constexpr int KBLKS = K_ / BK;
constexpr int X_BYTES = TA * BK * 2;
constexpr int UNIT_BYTES = BK * 32 * 4;
constexpr int SLAB_BYTES = BF * BK;
constexpr int STAGE_BYTES = X_BYTES + SLAB_BYTES;
constexpr int OFF_STG = STAGES * STAGE_BYTES;
constexpr int OFF_PL = OFF_STG + 3 * UNIT_BYTES;
constexpr int OFF_TAB = OFF_PL + 2048;
constexpr int OFF_BAR = OFF_STG + 65536;
constexpr int W_OFF = 16 * KBLKS * SLAB_BYTES;
constexpr int SMEM_BYTES = OFF_BAR + 512;
constexpr int NUM_CTAS = 132;
constexpr int NTHREADS = 384;
constexpr int NPACK = 3;
#define XT0 2600
#define WT0 2350
#define WTS 1000
#define S1D 400
#define PC 900
#define OB 32
#define WD 0x2212
#define RB 1
#define D0 900
#define LT0 7800
#define LTS 16
#define XPROM CU_TENSOR_MAP_L2_PROMOTION_L2_128B
#define QPROM CU_TENSOR_MAP_L2_PROMOTION_L2_128B
#define NP 3
#define PN 16
#define W17 1
#define SB0 0
#define NSB 8
#define FEN 1
#define GMAP 1
#define EPW 1
#define LCAP 14000
#define NB3 1
#define ORD 1
#define PU 36
#define U0(r, p) (ORD == 0 ? 3 * (r) + (p) : ORD == 1 ? 132 * (p) + (r) : (p) ? 131 + 2 * (r) + (p) : (r))
#define G0 WT0
#define G1 (WT0 + WTS)
#define G2 (WT0 + 2 * WTS)
#define G3 (WT0 + 3 * WTS)
#define G4 (WT0 + 4 * WTS)
#define G5 (WT0 + 5 * WTS)
constexpr uint64_t GATES = (uint64_t)(G0 / 32) << 8 | (uint64_t)(G1 / 32) << 16 | (uint64_t)(G2 / 32) << 24 | (uint64_t)(G3 / 32) << 32 | (uint64_t)(G4 / 32) << 40 | (uint64_t)(G5 / 32) << 48;
#define TR1 1
#define TR2 1
#define SW 0
#define XPD 2
#define XPS 2
#define XPW 1
#define SHF 1
#define PLF 1
#define EXF 1
#define PF 8
#define LD0 0
#define LPS 2
#define QD1 5
#define QN1 12
#define K0 4
#define QD0 3
#define QN0 8
#define FM0 0x100
#define K00 4
#define TCH 0
#define IX 8
#define UH 2
#define NA 13
#define UA 16
#define BF1 1
#define NTB 12
#define GB 7
#define W128 1
#define WP 0
#define RM 0x12
#define SMK 0xbaa9877654432110ull
#define SJ 0
#define DUP 1
#define T3 1
#define QD3 7
#define QN3 15
#define K3 6
#define HI 10
#define R24 0
#define UH3 1
#define K4 8
#define AD 2
#define BO 1
#define PEEL 0
#define TL 1
#define SLC 1
#define PADN 0
#define TOF 100
#define NX 2
#define WF 2
#define XPE 1
#define XP0 1600
#define XT2 0
#define XT3 0
#define THR 500
#define THS 50
#define W16 1
#define NBC 12
#define PAR 0
#define SWP 1
#define U0A 16
#define PKI -2
#define EW 1
#define TCN 12
#define WI 7
#define NSH 2
static_assert(SMEM_BYTES <= 232448, "smem");
static_assert(TB * 128 + 2 * SLAB_BYTES == STAGE_BYTES, "stage");
constexpr int B_FULL = 0, B_EMPTY = 4, B_DIR = 8, B_SLOT = 9, NBARS = 12, B_LAST = 16, B_SK = 32, B_RDY = B_DIR, B_W = 17, B_X = 18;
constexpr int OFF_EPOCH = OFF_BAR + 8 * NBARS;
constexpr uint32_t SB = 1024;
constexpr uint32_t UD = (SB >> 4) | (1u << 16);
enum { M_Q, M_D, M_XA, M_XC, M_XB, M_XD, M_O24, M_O32, M_O48, M_W, M_Q2, M_W2, NMAPS };

__device__ __align__(1024) uint8_t g_p[W_OFF + 12 * KBLKS * 2 * SLAB_BYTES];
__device__ __align__(128) unsigned int g_count[32 * 97];

__device__ __forceinline__ uint32_t smem_u32(const void* p) { return (uint32_t)__cvta_generic_to_shared(p); }
__device__ __forceinline__ void mbar_init(uint32_t bar, uint32_t cnt) {
  asm volatile("mbarrier.init.shared::cta.b64 [%0], %1;" ::"r"(bar), "r"(cnt) : "memory");
}
__device__ __forceinline__ void mbar_wait(uint32_t bar, uint32_t parity, uint32_t& c) {
  asm volatile(
      "{\n.reg .pred p;\n"
      "SPIN:\n"
      "mbarrier.try_wait.parity.shared::cta.b64 p, [%1], %2;\n"
      "add.u32 %0, %0, 1;\n"
      "setp.ge.or.u32 p, %0, 0x100000, p;\n"
      "@!p bra.uni SPIN;\n}\n"
      : "+r"(c) : "r"(bar), "r"(parity) : "memory");
}
__device__ __forceinline__ void mbar_wait_fast(uint32_t bar, uint32_t parity, uint32_t& c) {
  asm volatile(
      "{\n.reg .pred p;\n"
      "SPIN:\n"
      "mbarrier.try_wait.parity.shared::cta.b64 p, [%1], %2;\n"
      "@p bra.uni DONE;\n"
      "add.u32 %0, %0, 1;\n"
      "setp.lt.u32 p, %0, 0x100000;\n"
      "@p bra.uni SPIN;\n"
      "DONE:\n}\n"
      : "+r"(c) : "r"(bar), "r"(parity) : "memory");
}
__device__ __forceinline__ bool mbar_test(uint32_t bar, uint32_t parity) {
  uint32_t ok;
  asm volatile("{\n.reg .pred p;\nmbarrier.try_wait.parity.shared::cta.b64 p, [%1], %2;\nselp.u32 %0, 1, 0, p;\n}\n" : "=r"(ok) : "r"(bar), "r"(parity) : "memory");
  return ok != 0;
}
__device__ __forceinline__ bool mbar_peek(uint32_t bar, uint32_t parity) {
  uint32_t ok;
  asm volatile("{\n.reg .pred p;\nmbarrier.test_wait.parity.shared::cta.b64 p, [%1], %2;\nselp.u32 %0, 1, 0, p;\n}\n" : "=r"(ok) : "r"(bar), "r"(parity) : "memory");
  return ok != 0;
}
__device__ __forceinline__ void mbar_arrive(uint32_t bar) {
  asm volatile("mbarrier.arrive.shared::cta.b64 _, [%0];" ::"r"(bar) : "memory");
}
__device__ __forceinline__ uint32_t mapa(uint32_t a, uint32_t cta) {
  uint32_t r;
  asm("mapa.shared::cluster.u32 %0, %1, %2;" : "=r"(r) : "r"(a), "r"(cta));
  return r;
}
__device__ __forceinline__ void mbar_arrive_remote_if(uint32_t ra, uint32_t cond) {
  asm volatile("{\n.reg .pred p;\nsetp.ne.u32 p, %1, 0;\n@p mbarrier.arrive.shared::cluster.b64 _, [%0];\n}\n" ::"r"(ra), "r"(cond) : "memory");
}
#define ELECT "{\n.reg .pred p;\nelect.sync _|p, 0xffffffff;\n"
__device__ __forceinline__ void expect_w(uint32_t bar, uint32_t bytes) {
  asm volatile(ELECT "@p mbarrier.arrive.expect_tx.shared::cta.b64 _, [%0], %1;\n}\n" ::"r"(bar), "r"(bytes) : "memory");
}
__device__ __forceinline__ void arrive_w(uint32_t bar) {
  asm volatile(ELECT "@p mbarrier.arrive.shared::cta.b64 _, [%0];\n}\n" ::"r"(bar) : "memory");
}
__device__ __forceinline__ void tma_mc_w(uint32_t dst, const CUtensorMap* map, uint32_t bar, int c0, int c1) {
  asm volatile(
      ELECT "@p cp.async.bulk.tensor.2d.shared::cluster.global.mbarrier::complete_tx::bytes.multicast::cluster [%0], [%1, {%3, %4}], [%2], %5;\n}\n"
      ::"r"(dst), "l"((uint64_t)map), "r"(bar), "r"(c0), "r"(c1), "h"((uint16_t)3) : "memory");
}
__device__ __forceinline__ void wait_tma_mc_w(uint32_t wb, uint32_t parity, uint32_t& c, uint32_t dst, const CUtensorMap* map, uint32_t bar, int c0, int c1) {
  asm volatile(
      "{\n.reg .pred p;\n"
      "SPIN:\n"
      "mbarrier.try_wait.parity.shared::cta.b64 p, [%1], %2;\n"
      "add.u32 %0, %0, 1;\n"
      "setp.ge.or.u32 p, %0, 0x100000, p;\n"
      "@!p bra.uni SPIN;\n"
      "elect.sync _|p, 0xffffffff;\n"
      "@p cp.async.bulk.tensor.2d.shared::cluster.global.mbarrier::complete_tx::bytes.multicast::cluster [%3], [%4, {%6, %7}], [%5], %8;\n}\n"
      : "+r"(c) : "r"(wb), "r"(parity), "r"(dst), "l"((uint64_t)map), "r"(bar), "r"(c0), "r"(c1), "h"((uint16_t)3) : "memory");
}
__device__ __forceinline__ void bulk_w(uint32_t dst, const void* src, uint32_t bytes, uint32_t bar) {
  asm volatile(ELECT "@p cp.async.bulk.shared::cluster.global.mbarrier::complete_tx::bytes [%0], [%1], %2, [%3];\n}\n"
               ::"r"(dst), "l"(src), "r"(bytes), "r"(bar) : "memory");
}
__device__ __forceinline__ void tma_w(uint32_t dst, const CUtensorMap* map, uint32_t bar, int c0, int c1) {
  asm volatile(
      ELECT "@p cp.async.bulk.tensor.2d.shared::cluster.global.mbarrier::complete_tx::bytes [%0], [%1, {%3, %4}], [%2];\n}\n"
      ::"r"(dst), "l"((uint64_t)map), "r"(bar), "r"(c0), "r"(c1) : "memory");
}
__device__ __forceinline__ void tma3_w(uint32_t dst, const CUtensorMap* map, uint32_t bar, int c0, int c1, int c2) {
  asm volatile(
      ELECT "@p cp.async.bulk.tensor.3d.shared::cluster.global.mbarrier::complete_tx::bytes [%0], [%1, {%3, %4, %5}], [%2];\n}\n"
      ::"r"(dst), "l"((uint64_t)map), "r"(bar), "r"(c0), "r"(c1), "r"(c2) : "memory");
}
__device__ __forceinline__ void store_w(const CUtensorMap* map, uint32_t src, int c0, int c1) {
  asm volatile(ELECT "@p cp.async.bulk.tensor.2d.global.shared::cta.bulk_group [%0, {%2, %3}], [%1];\n}\n"
               "cp.async.bulk.commit_group;"
               ::"l"((uint64_t)map), "r"(src), "r"(c0), "r"(c1) : "memory");
}
__device__ __forceinline__ void bulk_wait_read() { asm volatile("cp.async.bulk.wait_group.read 0;" ::: "memory"); }
__device__ __forceinline__ void cluster_arrive_relaxed() { asm volatile("barrier.cluster.arrive.relaxed.aligned;" ::: "memory"); }
__device__ __forceinline__ void cluster_wait() { asm volatile("barrier.cluster.wait.acquire.aligned;" ::: "memory"); }
__device__ __forceinline__ void wgmma_fence() { asm volatile("wgmma.fence.sync.aligned;" ::: "memory"); }
__device__ __forceinline__ void wgmma_commit() { asm volatile("wgmma.commit_group.sync.aligned;" ::: "memory"); }
template <int N> __device__ __forceinline__ void wgmma_wait() { asm volatile("wgmma.wait_group.sync.aligned %0;" ::"n"(N) : "memory"); }
template <int N> __device__ __forceinline__ void fence_regs(float (&p)[N]) {
#pragma unroll
  for (int i = 0; i < N; i++) asm volatile("" : "+f"(p[i]) :: "memory");
}

template <int N> __device__ __forceinline__ void wgmma_rs(float* d, const uint32_t* a, uint32_t descB, uint32_t accum);
template <> __device__ __forceinline__ void wgmma_rs<40>(float* d, const uint32_t* a, uint32_t descB, uint32_t accum) {
  asm volatile(
    "{\n.reg .pred p;\n.reg .b64 db;\n"
    "setp.ne.b32 p, %25, 0;\n"
    "mov.b64 db, {%24, 0x40000040};\n"
    "wgmma.mma_async.sync.aligned.m64n40k16.f32.bf16.bf16 "
    "{%0, %1, %2, %3, %4, %5, %6, %7, %8, %9, %10, %11, %12, %13, %14, %15, %16, %17, %18, %19}, "
    "{%20, %21, %22, %23}, db, p, 1, 1, 0;\n"
    "}\n"
    : "+f"(d[0]), "+f"(d[1]), "+f"(d[2]), "+f"(d[3]), "+f"(d[4]), "+f"(d[5]), "+f"(d[6]), "+f"(d[7]), "+f"(d[8]), "+f"(d[9]), "+f"(d[10]), "+f"(d[11]), "+f"(d[12]), "+f"(d[13]), "+f"(d[14]), "+f"(d[15]), "+f"(d[16]), "+f"(d[17]), "+f"(d[18]), "+f"(d[19])
    : "r"(a[0]), "r"(a[1]), "r"(a[2]), "r"(a[3]), "r"(descB), "r"(accum));
}
template <> __device__ __forceinline__ void wgmma_rs<32>(float* d, const uint32_t* a, uint32_t descB, uint32_t accum) {
  asm volatile(
    "{\n.reg .pred p;\n.reg .b64 db;\n"
    "setp.ne.b32 p, %21, 0;\n"
    "mov.b64 db, {%20, 0x40000040};\n"
    "wgmma.mma_async.sync.aligned.m64n32k16.f32.bf16.bf16 "
    "{%0, %1, %2, %3, %4, %5, %6, %7, %8, %9, %10, %11, %12, %13, %14, %15}, "
    "{%16, %17, %18, %19}, db, p, 1, 1, 0;\n"
    "}\n"
    : "+f"(d[0]), "+f"(d[1]), "+f"(d[2]), "+f"(d[3]), "+f"(d[4]), "+f"(d[5]), "+f"(d[6]), "+f"(d[7]), "+f"(d[8]), "+f"(d[9]), "+f"(d[10]), "+f"(d[11]), "+f"(d[12]), "+f"(d[13]), "+f"(d[14]), "+f"(d[15])
    : "r"(a[0]), "r"(a[1]), "r"(a[2]), "r"(a[3]), "r"(descB), "r"(accum));
}
template <> __device__ __forceinline__ void wgmma_rs<24>(float* d, const uint32_t* a, uint32_t descB, uint32_t accum) {
  asm volatile(
    "{\n.reg .pred p;\n.reg .b64 db;\n"
    "setp.ne.b32 p, %17, 0;\n"
    "mov.b64 db, {%16, 0x40000040};\n"
    "wgmma.mma_async.sync.aligned.m64n24k16.f32.bf16.bf16 "
    "{%0, %1, %2, %3, %4, %5, %6, %7, %8, %9, %10, %11}, "
    "{%12, %13, %14, %15}, db, p, 1, 1, 0;\n"
    "}\n"
    : "+f"(d[0]), "+f"(d[1]), "+f"(d[2]), "+f"(d[3]), "+f"(d[4]), "+f"(d[5]), "+f"(d[6]), "+f"(d[7]), "+f"(d[8]), "+f"(d[9]), "+f"(d[10]), "+f"(d[11])
    : "r"(a[0]), "r"(a[1]), "r"(a[2]), "r"(a[3]), "r"(descB), "r"(accum));
}

template <int N> __device__ __forceinline__ void wgmma_rp(float* d, const uint32_t* a, uint64_t descB, uint32_t accum);
template <> __device__ __forceinline__ void wgmma_rp<256>(float* d, const uint32_t* a, uint64_t descB, uint32_t accum) {
  asm volatile(
    "{\n.reg .pred p;\n.reg .b64 db;\n"
    "setp.ne.b32 p, %133, 0;\n"
    "mov.b64 db, %132;\n"
    "wgmma.mma_async.sync.aligned.m64n256k16.f32.bf16.bf16 "
    "{%0, %1, %2, %3, %4, %5, %6, %7, %8, %9, %10, %11, %12, %13, %14, %15, %16, %17, %18, %19, %20, %21, %22, %23, %24, %25, %26, %27, %28, %29, %30, %31, %32, %33, %34, %35, %36, %37, %38, %39, %40, %41, %42, %43, %44, %45, %46, %47, %48, %49, %50, %51, %52, %53, %54, %55, %56, %57, %58, %59, %60, %61, %62, %63, %64, %65, %66, %67, %68, %69, %70, %71, %72, %73, %74, %75, %76, %77, %78, %79, %80, %81, %82, %83, %84, %85, %86, %87, %88, %89, %90, %91, %92, %93, %94, %95, %96, %97, %98, %99, %100, %101, %102, %103, %104, %105, %106, %107, %108, %109, %110, %111, %112, %113, %114, %115, %116, %117, %118, %119, %120, %121, %122, %123, %124, %125, %126, %127}, "
    "{%128, %129, %130, %131}, db, p, 1, 1, 0;\n"
    "}\n"
    : "+f"(d[0]), "+f"(d[1]), "+f"(d[2]), "+f"(d[3]), "+f"(d[4]), "+f"(d[5]), "+f"(d[6]), "+f"(d[7]), "+f"(d[8]), "+f"(d[9]), "+f"(d[10]), "+f"(d[11]), "+f"(d[12]), "+f"(d[13]), "+f"(d[14]), "+f"(d[15]), "+f"(d[16]), "+f"(d[17]), "+f"(d[18]), "+f"(d[19]), "+f"(d[20]), "+f"(d[21]), "+f"(d[22]), "+f"(d[23]), "+f"(d[24]), "+f"(d[25]), "+f"(d[26]), "+f"(d[27]), "+f"(d[28]), "+f"(d[29]), "+f"(d[30]), "+f"(d[31]), "+f"(d[32]), "+f"(d[33]), "+f"(d[34]), "+f"(d[35]), "+f"(d[36]), "+f"(d[37]), "+f"(d[38]), "+f"(d[39]), "+f"(d[40]), "+f"(d[41]), "+f"(d[42]), "+f"(d[43]), "+f"(d[44]), "+f"(d[45]), "+f"(d[46]), "+f"(d[47]), "+f"(d[48]), "+f"(d[49]), "+f"(d[50]), "+f"(d[51]), "+f"(d[52]), "+f"(d[53]), "+f"(d[54]), "+f"(d[55]), "+f"(d[56]), "+f"(d[57]), "+f"(d[58]), "+f"(d[59]), "+f"(d[60]), "+f"(d[61]), "+f"(d[62]), "+f"(d[63]), "+f"(d[64]), "+f"(d[65]), "+f"(d[66]), "+f"(d[67]), "+f"(d[68]), "+f"(d[69]), "+f"(d[70]), "+f"(d[71]), "+f"(d[72]), "+f"(d[73]), "+f"(d[74]), "+f"(d[75]), "+f"(d[76]), "+f"(d[77]), "+f"(d[78]), "+f"(d[79]), "+f"(d[80]), "+f"(d[81]), "+f"(d[82]), "+f"(d[83]), "+f"(d[84]), "+f"(d[85]), "+f"(d[86]), "+f"(d[87]), "+f"(d[88]), "+f"(d[89]), "+f"(d[90]), "+f"(d[91]), "+f"(d[92]), "+f"(d[93]), "+f"(d[94]), "+f"(d[95]), "+f"(d[96]), "+f"(d[97]), "+f"(d[98]), "+f"(d[99]), "+f"(d[100]), "+f"(d[101]), "+f"(d[102]), "+f"(d[103]), "+f"(d[104]), "+f"(d[105]), "+f"(d[106]), "+f"(d[107]), "+f"(d[108]), "+f"(d[109]), "+f"(d[110]), "+f"(d[111]), "+f"(d[112]), "+f"(d[113]), "+f"(d[114]), "+f"(d[115]), "+f"(d[116]), "+f"(d[117]), "+f"(d[118]), "+f"(d[119]), "+f"(d[120]), "+f"(d[121]), "+f"(d[122]), "+f"(d[123]), "+f"(d[124]), "+f"(d[125]), "+f"(d[126]), "+f"(d[127])
    : "r"(a[0]), "r"(a[1]), "r"(a[2]), "r"(a[3]), "l"(descB), "r"(accum));
}
template <> __device__ __forceinline__ void wgmma_rp<232>(float* d, const uint32_t* a, uint64_t descB, uint32_t accum) {
  asm volatile(
    "{\n.reg .pred p;\n.reg .b64 db;\n"
    "setp.ne.b32 p, %121, 0;\n"
    "mov.b64 db, %120;\n"
    "wgmma.mma_async.sync.aligned.m64n232k16.f32.bf16.bf16 "
    "{%0, %1, %2, %3, %4, %5, %6, %7, %8, %9, %10, %11, %12, %13, %14, %15, %16, %17, %18, %19, %20, %21, %22, %23, %24, %25, %26, %27, %28, %29, %30, %31, %32, %33, %34, %35, %36, %37, %38, %39, %40, %41, %42, %43, %44, %45, %46, %47, %48, %49, %50, %51, %52, %53, %54, %55, %56, %57, %58, %59, %60, %61, %62, %63, %64, %65, %66, %67, %68, %69, %70, %71, %72, %73, %74, %75, %76, %77, %78, %79, %80, %81, %82, %83, %84, %85, %86, %87, %88, %89, %90, %91, %92, %93, %94, %95, %96, %97, %98, %99, %100, %101, %102, %103, %104, %105, %106, %107, %108, %109, %110, %111, %112, %113, %114, %115}, "
    "{%116, %117, %118, %119}, db, p, 1, 1, 0;\n"
    "}\n"
    : "+f"(d[0]), "+f"(d[1]), "+f"(d[2]), "+f"(d[3]), "+f"(d[4]), "+f"(d[5]), "+f"(d[6]), "+f"(d[7]), "+f"(d[8]), "+f"(d[9]), "+f"(d[10]), "+f"(d[11]), "+f"(d[12]), "+f"(d[13]), "+f"(d[14]), "+f"(d[15]), "+f"(d[16]), "+f"(d[17]), "+f"(d[18]), "+f"(d[19]), "+f"(d[20]), "+f"(d[21]), "+f"(d[22]), "+f"(d[23]), "+f"(d[24]), "+f"(d[25]), "+f"(d[26]), "+f"(d[27]), "+f"(d[28]), "+f"(d[29]), "+f"(d[30]), "+f"(d[31]), "+f"(d[32]), "+f"(d[33]), "+f"(d[34]), "+f"(d[35]), "+f"(d[36]), "+f"(d[37]), "+f"(d[38]), "+f"(d[39]), "+f"(d[40]), "+f"(d[41]), "+f"(d[42]), "+f"(d[43]), "+f"(d[44]), "+f"(d[45]), "+f"(d[46]), "+f"(d[47]), "+f"(d[48]), "+f"(d[49]), "+f"(d[50]), "+f"(d[51]), "+f"(d[52]), "+f"(d[53]), "+f"(d[54]), "+f"(d[55]), "+f"(d[56]), "+f"(d[57]), "+f"(d[58]), "+f"(d[59]), "+f"(d[60]), "+f"(d[61]), "+f"(d[62]), "+f"(d[63]), "+f"(d[64]), "+f"(d[65]), "+f"(d[66]), "+f"(d[67]), "+f"(d[68]), "+f"(d[69]), "+f"(d[70]), "+f"(d[71]), "+f"(d[72]), "+f"(d[73]), "+f"(d[74]), "+f"(d[75]), "+f"(d[76]), "+f"(d[77]), "+f"(d[78]), "+f"(d[79]), "+f"(d[80]), "+f"(d[81]), "+f"(d[82]), "+f"(d[83]), "+f"(d[84]), "+f"(d[85]), "+f"(d[86]), "+f"(d[87]), "+f"(d[88]), "+f"(d[89]), "+f"(d[90]), "+f"(d[91]), "+f"(d[92]), "+f"(d[93]), "+f"(d[94]), "+f"(d[95]), "+f"(d[96]), "+f"(d[97]), "+f"(d[98]), "+f"(d[99]), "+f"(d[100]), "+f"(d[101]), "+f"(d[102]), "+f"(d[103]), "+f"(d[104]), "+f"(d[105]), "+f"(d[106]), "+f"(d[107]), "+f"(d[108]), "+f"(d[109]), "+f"(d[110]), "+f"(d[111]), "+f"(d[112]), "+f"(d[113]), "+f"(d[114]), "+f"(d[115])
    : "r"(a[0]), "r"(a[1]), "r"(a[2]), "r"(a[3]), "l"(descB), "r"(accum));
}

template <int N> __device__ __forceinline__ void wgmma_rl(float* d, const uint32_t* a, uint64_t descB);
template <> __device__ __forceinline__ void wgmma_rl<48>(float* d, const uint32_t* a, uint64_t descB) {
  asm volatile(
    "wgmma.mma_async.sync.aligned.m64n48k16.f32.bf16.bf16 "
    "{%0, %1, %2, %3, %4, %5, %6, %7, %8, %9, %10, %11, %12, %13, %14, %15, %16, %17, %18, %19, %20, %21, %22, %23}, "
    "{%24, %25, %26, %27}, %28, 1, 1, 1, 0;\n"
    : "+f"(d[0]), "+f"(d[1]), "+f"(d[2]), "+f"(d[3]), "+f"(d[4]), "+f"(d[5]), "+f"(d[6]), "+f"(d[7]), "+f"(d[8]), "+f"(d[9]), "+f"(d[10]), "+f"(d[11]), "+f"(d[12]), "+f"(d[13]), "+f"(d[14]), "+f"(d[15]), "+f"(d[16]), "+f"(d[17]), "+f"(d[18]), "+f"(d[19]), "+f"(d[20]), "+f"(d[21]), "+f"(d[22]), "+f"(d[23])
    : "r"(a[0]), "r"(a[1]), "r"(a[2]), "r"(a[3]), "l"(descB));
}
template <> __device__ __forceinline__ void wgmma_rl<32>(float* d, const uint32_t* a, uint64_t descB) {
  asm volatile(
    "wgmma.mma_async.sync.aligned.m64n32k16.f32.bf16.bf16 "
    "{%0, %1, %2, %3, %4, %5, %6, %7, %8, %9, %10, %11, %12, %13, %14, %15}, "
    "{%16, %17, %18, %19}, %20, 1, 1, 1, 0;\n"
    : "+f"(d[0]), "+f"(d[1]), "+f"(d[2]), "+f"(d[3]), "+f"(d[4]), "+f"(d[5]), "+f"(d[6]), "+f"(d[7]), "+f"(d[8]), "+f"(d[9]), "+f"(d[10]), "+f"(d[11]), "+f"(d[12]), "+f"(d[13]), "+f"(d[14]), "+f"(d[15])
    : "r"(a[0]), "r"(a[1]), "r"(a[2]), "r"(a[3]), "l"(descB));
}
template <> __device__ __forceinline__ void wgmma_rl<24>(float* d, const uint32_t* a, uint64_t descB) {
  asm volatile(
    "wgmma.mma_async.sync.aligned.m64n24k16.f32.bf16.bf16 "
    "{%0, %1, %2, %3, %4, %5, %6, %7, %8, %9, %10, %11}, "
    "{%12, %13, %14, %15}, %16, 1, 1, 1, 0;\n"
    : "+f"(d[0]), "+f"(d[1]), "+f"(d[2]), "+f"(d[3]), "+f"(d[4]), "+f"(d[5]), "+f"(d[6]), "+f"(d[7]), "+f"(d[8]), "+f"(d[9]), "+f"(d[10]), "+f"(d[11])
    : "r"(a[0]), "r"(a[1]), "r"(a[2]), "r"(a[3]), "l"(descB));
}
template <> __device__ __forceinline__ void wgmma_rl<232>(float* d, const uint32_t* a, uint64_t descB) {
  asm volatile(
    "wgmma.mma_async.sync.aligned.m64n232k16.f32.bf16.bf16 "
    "{%0, %1, %2, %3, %4, %5, %6, %7, %8, %9, %10, %11, %12, %13, %14, %15, %16, %17, %18, %19, %20, %21, %22, %23, %24, %25, %26, %27, %28, %29, %30, %31, %32, %33, %34, %35, %36, %37, %38, %39, %40, %41, %42, %43, %44, %45, %46, %47, %48, %49, %50, %51, %52, %53, %54, %55, %56, %57, %58, %59, %60, %61, %62, %63, %64, %65, %66, %67, %68, %69, %70, %71, %72, %73, %74, %75, %76, %77, %78, %79, %80, %81, %82, %83, %84, %85, %86, %87, %88, %89, %90, %91, %92, %93, %94, %95, %96, %97, %98, %99, %100, %101, %102, %103, %104, %105, %106, %107, %108, %109, %110, %111, %112, %113, %114, %115}, "
    "{%116, %117, %118, %119}, %120, 1, 1, 1, 0;\n"
    : "+f"(d[0]), "+f"(d[1]), "+f"(d[2]), "+f"(d[3]), "+f"(d[4]), "+f"(d[5]), "+f"(d[6]), "+f"(d[7]), "+f"(d[8]), "+f"(d[9]), "+f"(d[10]), "+f"(d[11]), "+f"(d[12]), "+f"(d[13]), "+f"(d[14]), "+f"(d[15]), "+f"(d[16]), "+f"(d[17]), "+f"(d[18]), "+f"(d[19]), "+f"(d[20]), "+f"(d[21]), "+f"(d[22]), "+f"(d[23]), "+f"(d[24]), "+f"(d[25]), "+f"(d[26]), "+f"(d[27]), "+f"(d[28]), "+f"(d[29]), "+f"(d[30]), "+f"(d[31]), "+f"(d[32]), "+f"(d[33]), "+f"(d[34]), "+f"(d[35]), "+f"(d[36]), "+f"(d[37]), "+f"(d[38]), "+f"(d[39]), "+f"(d[40]), "+f"(d[41]), "+f"(d[42]), "+f"(d[43]), "+f"(d[44]), "+f"(d[45]), "+f"(d[46]), "+f"(d[47]), "+f"(d[48]), "+f"(d[49]), "+f"(d[50]), "+f"(d[51]), "+f"(d[52]), "+f"(d[53]), "+f"(d[54]), "+f"(d[55]), "+f"(d[56]), "+f"(d[57]), "+f"(d[58]), "+f"(d[59]), "+f"(d[60]), "+f"(d[61]), "+f"(d[62]), "+f"(d[63]), "+f"(d[64]), "+f"(d[65]), "+f"(d[66]), "+f"(d[67]), "+f"(d[68]), "+f"(d[69]), "+f"(d[70]), "+f"(d[71]), "+f"(d[72]), "+f"(d[73]), "+f"(d[74]), "+f"(d[75]), "+f"(d[76]), "+f"(d[77]), "+f"(d[78]), "+f"(d[79]), "+f"(d[80]), "+f"(d[81]), "+f"(d[82]), "+f"(d[83]), "+f"(d[84]), "+f"(d[85]), "+f"(d[86]), "+f"(d[87]), "+f"(d[88]), "+f"(d[89]), "+f"(d[90]), "+f"(d[91]), "+f"(d[92]), "+f"(d[93]), "+f"(d[94]), "+f"(d[95]), "+f"(d[96]), "+f"(d[97]), "+f"(d[98]), "+f"(d[99]), "+f"(d[100]), "+f"(d[101]), "+f"(d[102]), "+f"(d[103]), "+f"(d[104]), "+f"(d[105]), "+f"(d[106]), "+f"(d[107]), "+f"(d[108]), "+f"(d[109]), "+f"(d[110]), "+f"(d[111]), "+f"(d[112]), "+f"(d[113]), "+f"(d[114]), "+f"(d[115])
    : "r"(a[0]), "r"(a[1]), "r"(a[2]), "r"(a[3]), "l"(descB));
}
template <> __device__ __forceinline__ void wgmma_rl<256>(float* d, const uint32_t* a, uint64_t descB) {
  asm volatile(
    "wgmma.mma_async.sync.aligned.m64n256k16.f32.bf16.bf16 "
    "{%0, %1, %2, %3, %4, %5, %6, %7, %8, %9, %10, %11, %12, %13, %14, %15, %16, %17, %18, %19, %20, %21, %22, %23, %24, %25, %26, %27, %28, %29, %30, %31, %32, %33, %34, %35, %36, %37, %38, %39, %40, %41, %42, %43, %44, %45, %46, %47, %48, %49, %50, %51, %52, %53, %54, %55, %56, %57, %58, %59, %60, %61, %62, %63, %64, %65, %66, %67, %68, %69, %70, %71, %72, %73, %74, %75, %76, %77, %78, %79, %80, %81, %82, %83, %84, %85, %86, %87, %88, %89, %90, %91, %92, %93, %94, %95, %96, %97, %98, %99, %100, %101, %102, %103, %104, %105, %106, %107, %108, %109, %110, %111, %112, %113, %114, %115, %116, %117, %118, %119, %120, %121, %122, %123, %124, %125, %126, %127}, "
    "{%128, %129, %130, %131}, %132, 1, 1, 1, 0;\n"
    : "+f"(d[0]), "+f"(d[1]), "+f"(d[2]), "+f"(d[3]), "+f"(d[4]), "+f"(d[5]), "+f"(d[6]), "+f"(d[7]), "+f"(d[8]), "+f"(d[9]), "+f"(d[10]), "+f"(d[11]), "+f"(d[12]), "+f"(d[13]), "+f"(d[14]), "+f"(d[15]), "+f"(d[16]), "+f"(d[17]), "+f"(d[18]), "+f"(d[19]), "+f"(d[20]), "+f"(d[21]), "+f"(d[22]), "+f"(d[23]), "+f"(d[24]), "+f"(d[25]), "+f"(d[26]), "+f"(d[27]), "+f"(d[28]), "+f"(d[29]), "+f"(d[30]), "+f"(d[31]), "+f"(d[32]), "+f"(d[33]), "+f"(d[34]), "+f"(d[35]), "+f"(d[36]), "+f"(d[37]), "+f"(d[38]), "+f"(d[39]), "+f"(d[40]), "+f"(d[41]), "+f"(d[42]), "+f"(d[43]), "+f"(d[44]), "+f"(d[45]), "+f"(d[46]), "+f"(d[47]), "+f"(d[48]), "+f"(d[49]), "+f"(d[50]), "+f"(d[51]), "+f"(d[52]), "+f"(d[53]), "+f"(d[54]), "+f"(d[55]), "+f"(d[56]), "+f"(d[57]), "+f"(d[58]), "+f"(d[59]), "+f"(d[60]), "+f"(d[61]), "+f"(d[62]), "+f"(d[63]), "+f"(d[64]), "+f"(d[65]), "+f"(d[66]), "+f"(d[67]), "+f"(d[68]), "+f"(d[69]), "+f"(d[70]), "+f"(d[71]), "+f"(d[72]), "+f"(d[73]), "+f"(d[74]), "+f"(d[75]), "+f"(d[76]), "+f"(d[77]), "+f"(d[78]), "+f"(d[79]), "+f"(d[80]), "+f"(d[81]), "+f"(d[82]), "+f"(d[83]), "+f"(d[84]), "+f"(d[85]), "+f"(d[86]), "+f"(d[87]), "+f"(d[88]), "+f"(d[89]), "+f"(d[90]), "+f"(d[91]), "+f"(d[92]), "+f"(d[93]), "+f"(d[94]), "+f"(d[95]), "+f"(d[96]), "+f"(d[97]), "+f"(d[98]), "+f"(d[99]), "+f"(d[100]), "+f"(d[101]), "+f"(d[102]), "+f"(d[103]), "+f"(d[104]), "+f"(d[105]), "+f"(d[106]), "+f"(d[107]), "+f"(d[108]), "+f"(d[109]), "+f"(d[110]), "+f"(d[111]), "+f"(d[112]), "+f"(d[113]), "+f"(d[114]), "+f"(d[115]), "+f"(d[116]), "+f"(d[117]), "+f"(d[118]), "+f"(d[119]), "+f"(d[120]), "+f"(d[121]), "+f"(d[122]), "+f"(d[123]), "+f"(d[124]), "+f"(d[125]), "+f"(d[126]), "+f"(d[127])
    : "r"(a[0]), "r"(a[1]), "r"(a[2]), "r"(a[3]), "l"(descB));
}

template <int N> __device__ __forceinline__ void wgmma_ss(float* d, uint64_t descA, uint64_t descB, uint32_t accum);
template <> __device__ __forceinline__ void wgmma_ss<192>(float* d, uint64_t descA, uint64_t descB, uint32_t accum) {
  asm volatile(
    "{\n.reg .pred p;\n"
    "setp.ne.b32 p, %98, 0;\n"
    "wgmma.mma_async.sync.aligned.m64n192k16.f32.bf16.bf16 "
    "{%0, %1, %2, %3, %4, %5, %6, %7, %8, %9, %10, %11, %12, %13, %14, %15, %16, %17, %18, %19, %20, %21, %22, %23, %24, %25, %26, %27, %28, %29, %30, %31, %32, %33, %34, %35, %36, %37, %38, %39, %40, %41, %42, %43, %44, %45, %46, %47, %48, %49, %50, %51, %52, %53, %54, %55, %56, %57, %58, %59, %60, %61, %62, %63, %64, %65, %66, %67, %68, %69, %70, %71, %72, %73, %74, %75, %76, %77, %78, %79, %80, %81, %82, %83, %84, %85, %86, %87, %88, %89, %90, %91, %92, %93, %94, %95}, "
    "%96, %97, p, 1, 1, 0, 0;\n"
    "}\n"
    : "+f"(d[0]), "+f"(d[1]), "+f"(d[2]), "+f"(d[3]), "+f"(d[4]), "+f"(d[5]), "+f"(d[6]), "+f"(d[7]), "+f"(d[8]), "+f"(d[9]), "+f"(d[10]), "+f"(d[11]), "+f"(d[12]), "+f"(d[13]), "+f"(d[14]), "+f"(d[15]), "+f"(d[16]), "+f"(d[17]), "+f"(d[18]), "+f"(d[19]), "+f"(d[20]), "+f"(d[21]), "+f"(d[22]), "+f"(d[23]), "+f"(d[24]), "+f"(d[25]), "+f"(d[26]), "+f"(d[27]), "+f"(d[28]), "+f"(d[29]), "+f"(d[30]), "+f"(d[31]), "+f"(d[32]), "+f"(d[33]), "+f"(d[34]), "+f"(d[35]), "+f"(d[36]), "+f"(d[37]), "+f"(d[38]), "+f"(d[39]), "+f"(d[40]), "+f"(d[41]), "+f"(d[42]), "+f"(d[43]), "+f"(d[44]), "+f"(d[45]), "+f"(d[46]), "+f"(d[47]), "+f"(d[48]), "+f"(d[49]), "+f"(d[50]), "+f"(d[51]), "+f"(d[52]), "+f"(d[53]), "+f"(d[54]), "+f"(d[55]), "+f"(d[56]), "+f"(d[57]), "+f"(d[58]), "+f"(d[59]), "+f"(d[60]), "+f"(d[61]), "+f"(d[62]), "+f"(d[63]), "+f"(d[64]), "+f"(d[65]), "+f"(d[66]), "+f"(d[67]), "+f"(d[68]), "+f"(d[69]), "+f"(d[70]), "+f"(d[71]), "+f"(d[72]), "+f"(d[73]), "+f"(d[74]), "+f"(d[75]), "+f"(d[76]), "+f"(d[77]), "+f"(d[78]), "+f"(d[79]), "+f"(d[80]), "+f"(d[81]), "+f"(d[82]), "+f"(d[83]), "+f"(d[84]), "+f"(d[85]), "+f"(d[86]), "+f"(d[87]), "+f"(d[88]), "+f"(d[89]), "+f"(d[90]), "+f"(d[91]), "+f"(d[92]), "+f"(d[93]), "+f"(d[94]), "+f"(d[95])
    : "l"(descA), "l"(descB), "r"(accum));
}
template <> __device__ __forceinline__ void wgmma_ss<184>(float* d, uint64_t descA, uint64_t descB, uint32_t accum) {
  asm volatile(
    "{\n.reg .pred p;\n"
    "setp.ne.b32 p, %94, 0;\n"
    "wgmma.mma_async.sync.aligned.m64n184k16.f32.bf16.bf16 "
    "{%0, %1, %2, %3, %4, %5, %6, %7, %8, %9, %10, %11, %12, %13, %14, %15, %16, %17, %18, %19, %20, %21, %22, %23, %24, %25, %26, %27, %28, %29, %30, %31, %32, %33, %34, %35, %36, %37, %38, %39, %40, %41, %42, %43, %44, %45, %46, %47, %48, %49, %50, %51, %52, %53, %54, %55, %56, %57, %58, %59, %60, %61, %62, %63, %64, %65, %66, %67, %68, %69, %70, %71, %72, %73, %74, %75, %76, %77, %78, %79, %80, %81, %82, %83, %84, %85, %86, %87, %88, %89, %90, %91}, "
    "%92, %93, p, 1, 1, 0, 0;\n"
    "}\n"
    : "+f"(d[0]), "+f"(d[1]), "+f"(d[2]), "+f"(d[3]), "+f"(d[4]), "+f"(d[5]), "+f"(d[6]), "+f"(d[7]), "+f"(d[8]), "+f"(d[9]), "+f"(d[10]), "+f"(d[11]), "+f"(d[12]), "+f"(d[13]), "+f"(d[14]), "+f"(d[15]), "+f"(d[16]), "+f"(d[17]), "+f"(d[18]), "+f"(d[19]), "+f"(d[20]), "+f"(d[21]), "+f"(d[22]), "+f"(d[23]), "+f"(d[24]), "+f"(d[25]), "+f"(d[26]), "+f"(d[27]), "+f"(d[28]), "+f"(d[29]), "+f"(d[30]), "+f"(d[31]), "+f"(d[32]), "+f"(d[33]), "+f"(d[34]), "+f"(d[35]), "+f"(d[36]), "+f"(d[37]), "+f"(d[38]), "+f"(d[39]), "+f"(d[40]), "+f"(d[41]), "+f"(d[42]), "+f"(d[43]), "+f"(d[44]), "+f"(d[45]), "+f"(d[46]), "+f"(d[47]), "+f"(d[48]), "+f"(d[49]), "+f"(d[50]), "+f"(d[51]), "+f"(d[52]), "+f"(d[53]), "+f"(d[54]), "+f"(d[55]), "+f"(d[56]), "+f"(d[57]), "+f"(d[58]), "+f"(d[59]), "+f"(d[60]), "+f"(d[61]), "+f"(d[62]), "+f"(d[63]), "+f"(d[64]), "+f"(d[65]), "+f"(d[66]), "+f"(d[67]), "+f"(d[68]), "+f"(d[69]), "+f"(d[70]), "+f"(d[71]), "+f"(d[72]), "+f"(d[73]), "+f"(d[74]), "+f"(d[75]), "+f"(d[76]), "+f"(d[77]), "+f"(d[78]), "+f"(d[79]), "+f"(d[80]), "+f"(d[81]), "+f"(d[82]), "+f"(d[83]), "+f"(d[84]), "+f"(d[85]), "+f"(d[86]), "+f"(d[87]), "+f"(d[88]), "+f"(d[89]), "+f"(d[90]), "+f"(d[91])
    : "l"(descA), "l"(descB), "r"(accum));
}

template <int N> struct IC { static constexpr int v = N; };

__device__ __forceinline__ void stmatrix_x4_t(uint32_t addr, uint32_t r0, uint32_t r1, uint32_t r2, uint32_t r3) {
  asm volatile("stmatrix.sync.aligned.m8n8.x4.trans.shared.b16 [%0], {%1, %2, %3, %4};"
               ::"r"(addr), "r"(r0), "r"(r1), "r"(r2), "r"(r3) : "memory");
}
__device__ __forceinline__ void ldmatrix_x4(uint32_t* r, uint32_t addr) {
  asm volatile("ldmatrix.sync.aligned.m8n8.x4.shared.b16 {%0, %1, %2, %3}, [%4];"
               : "=r"(r[0]), "=r"(r[1]), "=r"(r[2]), "=r"(r[3]) : "r"(addr) : "memory");
}
__device__ __forceinline__ void ldmatrix_x4_if(uint32_t* r, uint32_t addr, uint32_t c) {
  asm volatile("{\n.reg .pred p;\nsetp.eq.u32 p, %5, 0;\n@p ldmatrix.sync.aligned.m8n8.x4.shared.b16 {%0, %1, %2, %3}, [%4];\n}\n"
               : "+r"(r[0]), "+r"(r[1]), "+r"(r[2]), "+r"(r[3]) : "r"(addr), "r"(c) : "memory");
}
__device__ __forceinline__ uint32_t pack_bf16(float a, float b) {
  __nv_bfloat162 v = __floats2bfloat162_rn(a, b);
  return *reinterpret_cast<uint32_t*>(&v);
}
__device__ __forceinline__ uint32_t prmt(uint32_t a, uint32_t b, uint32_t s) {
  uint32_t d;
  asm("prmt.b32 %0, %1, %2, %3;" : "=r"(d) : "r"(a), "r"(b), "r"(s));
  return d;
}
__device__ __forceinline__ uint32_t lds32(uint32_t a) {
  uint32_t v;
  asm volatile("ld.shared.u32 %0, [%1];" : "=r"(v) : "r"(a) : "memory");
  return v;
}
__device__ __forceinline__ void lds128(uint32_t* v, uint32_t a) {
  asm volatile("ld.shared.v4.u32 {%0, %1, %2, %3}, [%4];" : "=r"(v[0]), "=r"(v[1]), "=r"(v[2]), "=r"(v[3]) : "r"(a) : "memory");
}
__device__ __forceinline__ void sts128(uint32_t a, const uint32_t* v) {
  asm volatile("st.shared.v4.u32 [%0], {%1, %2, %3, %4};" ::"r"(a), "r"(v[0]), "r"(v[1]), "r"(v[2]), "r"(v[3]) : "memory");
}
__device__ __forceinline__ void sts32(uint32_t a, uint32_t v) {
  asm volatile("st.shared.u32 [%0], %1;" ::"r"(a), "r"(v) : "memory");
}
__device__ __forceinline__ void wait_until(uint32_t t0, uint32_t at) {
  asm volatile(
      "{\n.reg .pred p;\n.reg .s32 r;\n"
      "SPIN:\n"
      "mov.u32 r, %%clock;\n"
      "sub.s32 r, %0, r;\n"
      "setp.gt.s32 p, r, 0;\n"
      "shr.s32 r, r, %1;\n"
      "@p nanosleep.u32 r;\n"
      "@p bra.uni SPIN;\n}\n"
      ::"r"(t0 + at), "n"(NSH) : "memory");
}
__device__ __forceinline__ void wait_exact(uint32_t t0, uint32_t at) {
  if (!THR) return wait_until(t0, at);
  asm volatile(
      "{\n.reg .pred p, q;\n.reg .s32 r;\n"
      "SPIN:\n"
      "mov.u32 r, %%clock;\n"
      "sub.s32 r, %0, r;\n"
      "setp.gt.s32 p, r, 0;\n"
      "setp.gt.s32 q, r, %1;\n"
      "@q nanosleep.u32 %2;\n"
      "@p bra.uni SPIN;\n}\n"
      ::"r"(t0 + at), "n"(THR), "n"(THS) : "memory");
}
__device__ __forceinline__ void spin_until(uint32_t t0, uint32_t at) {
  while ((int)((uint32_t)clock() - t0) < (int)at) {}
}
__device__ __forceinline__ void wait_count(const unsigned int* f, uint32_t& c) {
  asm volatile(
      "{\n.reg .pred p;\n.reg .u32 v;\n"
      "SPIN:\n"
      "ld.acquire.gpu.global.u32 v, [%1];\n"
      "add.u32 %0, %0, 16;\n"
      "setp.lt.u32 p, %0, 0x100000;\n"
      "setp.lt.and.u32 p, v, 64, p;\n"
      "@p nanosleep.u32 100;\n"
      "@p bra.uni SPIN;\n}\n"
      : "+r"(c) : "l"(f) : "memory");
}
template <int E>
__device__ __forceinline__ void ld_lut(uint32_t* v, const __nv_bfloat16* p) {
  asm volatile("ld.global.nc.u32 %0, [%1+%2];" : "=r"(v[E]) : "l"(p), "n"(((E & 3) * N_ + 8 * (E >> 2)) * 2));
  if constexpr (E < 7) ld_lut<E + 1>(v, p);
}
template <int OFF>
__device__ __forceinline__ void ld_codes4(uint32_t* w, const int* p) {
  asm volatile("ld.global.nc.L1::no_allocate.v4.u32 {%0, %1, %2, %3}, [%4+%5];" : "=r"(w[0]), "=r"(w[1]), "=r"(w[2]), "=r"(w[3]) : "l"(p), "n"(OFF));
}
__device__ __forceinline__ void ld_codes(uint32_t* w, const int* p) {
  ld_codes4<0>(w, p);
  ld_codes4<N_ * 4>(w + 4, p);
  ld_codes4<N_ * 32>(w + 8, p);
  ld_codes4<N_ * 36>(w + 12, p);
}
__device__ __forceinline__ void prefetch_map(const CUtensorMap* map) {
  asm volatile("prefetch.tensormap [%0];" ::"l"((uint64_t)map) : "memory");
}
template <int OFF>
__device__ __forceinline__ void ld_words(uint32_t* w, const uint8_t* p) {
  asm volatile("ld.relaxed.gpu.global.v4.u32 {%0, %1, %2, %3}, [%4+%5];" : "=r"(w[0]), "=r"(w[1]), "=r"(w[2]), "=r"(w[3]) : "l"(p), "n"(OFF) : "memory");
}
template <int OFF>
__device__ __forceinline__ void st_words(uint8_t* p, const uint32_t* w) {
  asm volatile("st.relaxed.gpu.global.v4.u32 [%0+%5], {%1, %2, %3, %4};" ::"l"(p), "r"(w[0]), "r"(w[1]), "r"(w[2]), "r"(w[3]), "n"(OFF) : "memory");
}

#define DBGR(i, j)
#define DBG(i)

__device__ __forceinline__ uint32_t word_key(uint32_t odd) { return 0xcdf00000u + (odd << 19); }
__device__ __forceinline__ uint32_t make_word(uint32_t c0, uint32_t c1, uint32_t c2, uint32_t c3, uint32_t key) {
  uint32_t p01, p23, n, w;
  asm("mad.lo.u32 %0, %1, 16, %2;" : "=r"(p01) : "r"(c1), "r"(c0));
  asm("mad.lo.u32 %0, %1, 16, %2;" : "=r"(p23) : "r"(c3), "r"(c2));
  asm("mad.lo.u32 %0, %1, 256, %2;" : "=r"(n) : "r"(p23), "r"(p01));
  asm("mad.lo.u32 %0, %1, 0x7fff, %2;" : "=r"(w) : "r"((n & 0x8888u) | key), "r"(n));
  return w;
}
struct Planes { uint32_t v[4][4]; };
__device__ __forceinline__ void lookup4(const Planes& pl, int c, uint32_t s, uint32_t sc, uint32_t& o0, uint32_t& o1) {
  uint32_t s2;
  asm("{\n.reg .b16 l, h;\n.reg .b32 t;\nmov.b32 {l, h}, %1;\nmov.b32 t, {h, h};\nmul.rn.f16x2 %0, t, %2;\n}\n" : "=r"(s2) : "r"(s), "r"(sc));
  const uint32_t lo = prmt(prmt(pl.v[0][2 * c], pl.v[1][2 * c], s), prmt(pl.v[2][2 * c], pl.v[3][2 * c], s), s2);
  const uint32_t hi = prmt(prmt(pl.v[0][2 * c + 1], pl.v[1][2 * c + 1], s), prmt(pl.v[2][2 * c + 1], pl.v[3][2 * c + 1], s), s2);
  o0 = prmt(lo, hi, 0x5140);
  o1 = prmt(lo, hi, 0x7362);
}
__device__ __forceinline__ void store_planes(uint32_t dst, const uint32_t* lv) {
#pragma unroll
  for (int h = 0; h < 2; h++) {
    uint32_t qp[4];
#pragma unroll
    for (int c = 0; c < 2; c++) {
      const uint32_t a = prmt(lv[4 * c], lv[4 * c + 1], h ? 0x7362 : 0x5140), b = prmt(lv[4 * c + 2], lv[4 * c + 3], h ? 0x7362 : 0x5140);
      qp[2 * c] = prmt(a, b, 0x5410);
      qp[2 * c + 1] = prmt(a, b, 0x7632);
    }
    sts128(dst + 64 * h, qp);
  }
}
__device__ __forceinline__ bool words_ok(const uint32_t* P, uint32_t tag) {
  if (W16) return (P[0] & P[4] & tag) != 0;
  return (P[0] & P[1] & P[2] & P[3] & P[4] & P[5] & P[6] & P[7] & tag) != 0;
}
template <int NJ>
__device__ __forceinline__ void stage_part(const float* a, uint32_t sts) {
#pragma unroll
  for (int j = 0; j < NJ; j++)
    stmatrix_x4_t(sts + 16 * j * 128, pack_bf16(a[8 * j], a[8 * j + 1]), pack_bf16(a[8 * j + 2], a[8 * j + 3]),
                  pack_bf16(a[8 * j + 4], a[8 * j + 5]), pack_bf16(a[8 * j + 6], a[8 * j + 7]));
}

template <int OFF>
__device__ __forceinline__ uint32_t lut_at(uint32_t tab, uint32_t c) {
  uint32_t v;
  asm volatile("ld.shared.u16 %0, [%1+%2];" : "=r"(v) : "r"(tab + 40 * c), "n"(OFF));
  return v;
}
template <int J>
__device__ __forceinline__ void convert_col(const uint32_t (*v)[4], uint32_t tab, uint8_t* dst) {
  uint32_t o[4];
#pragma unroll
  for (int i = 0; i < 4; i++) {
    const uint32_t a = lut_at<2 * J>(tab, v[2 * i][J]), b = lut_at<2 * J>(tab, v[2 * i + 1][J]);
    asm("mad.lo.u32 %0, %1, 65536, %2;" : "=r"(o[i]) : "r"(b), "r"(a));
  }
  st_words<2048 * J>(dst, o);
}

template <int J>
__device__ __forceinline__ void convert_shfl(const uint32_t (*v)[4], uint32_t e, uint8_t* dst) {
  uint32_t o[4];
#pragma unroll
  for (int i = 0; i < 4; i++) {
    uint32_t a, b;
    asm volatile("shfl.sync.idx.b32 %0, %1, %2, 0x101f, 0xffffffff;" : "=r"(a) : "r"(e), "r"(v[2 * i][J]));
    asm volatile("shfl.sync.idx.b32 %0, %1, %2, 0x101f, 0xffffffff;" : "=r"(b) : "r"(e), "r"(v[2 * i + 1][J]));
    o[i] = prmt(a, b, J & 1 ? 0x7632 : 0x5410);
  }
  st_words<2048 * J>(dst, o);
}

struct Maps { CUtensorMap m[NMAPS]; uint64_t desc[6]; const __nv_bfloat16* lut; uint64_t pad; uint32_t tiles[66], jobs[396]; };
struct Tab { uint32_t tiles[66], jobs[396]; };
constexpr int imin(int a, int b) { return a < b ? a : b; }
constexpr Tab make_tab() {
  Tab m{};
  for (int t = 0; t < 66; t++) {
    const int u = t - 32, g = t < 32 ? t & 7 : 1 + u % 7, j = t < 32 ? t >> 3 : 4 + u / 7;
    int cl = t >= 60 ? (int)((0x413B3F394035ull >> (8 * (t - 60))) & 0xff) : g == GB ? 48 + 2 * j : g ? 6 * j + g - 1 - (g > GB) : imin(49 + 6 * j, 87 - 12 * j);
    if (GMAP == 0) cl = (t + 4) % 66;
    const int yi = cl / 6, fb = 2 * (cl % 6);
    const int fa = cl < 48 ? fb : 12 + 2 * (cl & 1), ta = cl < 48 ? TA * yi : imin(TC * ((cl - 48) >> 1), M_ - TC);
    m.tiles[t >= 62 ? t & 3 : t + 4] = fa | fb << 4 | ta << 5 | (TD * yi - (TB - TD) * imin(8 - yi, 0)) << 13;
  }
  int third[396] = {}, t2[396] = {}, by[896] = {}, nt = 0, na = 0;
  for (int i = 0; i < 396; i++) t2[i] = 1;
  for (int b = 0, k = 0; b < 132; b++) {
    if ((m.tiles[b / 2] & 15) < 12) continue;
    third[3 * b] = (k / 2 + 1) * NBC / 36 != (k / 2) * NBC / 36;
    if (third[3 * b] && (nt / 2 + 1) * NTB / NBC != (nt / 2) * NTB / NBC) t2[3 * b] = 0;
    nt += third[3 * b];
    k++;
  }
  const int need = 104 - nt;
  for (int b = 0, k = 0; b < 132; b++) {
    if ((m.tiles[b / 2] & 15) >= 12) continue;
    if ((na / 2 + 1) * need / 96 != (na / 2) * need / 96) {
      third[3 * b] = 1;
      if (k < 12 - NTB) t2[3 * b] = 0;
      k++;
    }
    na++;
  }
  int u = 920, l = 0;
  for (int pass = 0; pass < 2; pass++)
    for (int i = 0; i < 396; i++) {
      if (BF1 ? ((m.tiles[i / 6] & 15) >= 12) == pass : pass) continue;
      m.jobs[i] = third[i] ? u++ : 1024;
      by[third[i] ? m.jobs[i] - 128 : 396 + U0(i / 3, i % 3)] = i + 1;
    }
  for (int k = 0; k < 896; k++) {
    const int i = by[k] - 1;
    if (i < 0) continue;
    if (t2[i]) m.jobs[i] |= l << 11 | imin(LCAP, LT0 + l * LTS) / 8 << 20, l++;
    else m.jobs[i] |= 384 << 11;
  }
  if (l != 384 || u != 1024) m.jobs[400] = 0;
  return m;
}

#define TILES() \
  const int fta = (te & 15) + rank, ftb = ((te >> 4) & 15) + rank, toka = (te >> 5) & 0x7f8, tokb = (te >> 13) & 0x7f8; \
  const bool big = fta < 12; \
  (void)toka; (void)big; (void)tokb; (void)ftb
__global__ void __cluster_dims__(2, 1, 1) __launch_bounds__(NTHREADS, 1)
fused_kernel(unsigned int* __restrict__ count, const __nv_bfloat16* __restrict__ lut, uint8_t* __restrict__ gp,
             const int* __restrict__ qw, const uint8_t* __restrict__ xg, uint64_t desc1, const __grid_constant__ Maps maps) {
  extern __shared__ __align__(1024) uint8_t smem_gen[];
  const uint32_t t0 = clock() + TOF;
  const int tid = threadIdx.x;
  uint32_t cf[16];
  const int* src = qw + (((tid >> 8) * BK + 32 + (tid & 48) + ((tid >> 1) & 6)) * N_ + (blockIdx.x & 127) * 16 + (tid & 3) * 4);
  uint32_t ep0 = 0;
  if ((tid >> 6) == 2) {
    if (EPW) asm volatile("ld.relaxed.gpu.global.u32 %0, [%1];" : "=r"(ep0) : "l"(count) : "memory");
    ld_codes(cf, src);
  }
  const uint32_t te = maps.tiles[blockIdx.x >> 1];
  const int rank = blockIdx.x & 1;
  uint32_t sl;
  asm("mul.lo.u32 %0, %1, 0x1000000;" : "=r"(sl) : "r"(rank));
  sl += SB;
  auto bar = [&](int i) { return sl + OFF_BAR + 8 * i; };
  const int w12 = __shfl_sync(0xffffffffu, tid >> 5, 0);
  const int wg = w12 >> 2;
  const int warp = w12 & 3;
  const int lane = tid & 31;
  uint32_t bud = 0;
  if (__builtin_expect(wg == 0, 1)) {
    asm volatile("setmaxnreg.dec.sync.aligned.u32 72;");
    if (warp == 0) {
      if (lane == 0) {
#pragma unroll
        for (int i = 0; i < NBARS; i++) mbar_init(bar(i), i >= 4 && i < 8 ? 4 : 1);
        mbar_init(bar(B_LAST), 4);
        mbar_init(bar(B_W), 1);
        mbar_init(bar(B_SK), 128);
        for (int i = 1; i <= NX; i++) mbar_init(bar(B_X * i), 1);
        asm volatile("fence.mbarrier_init.release.cluster;" ::: "memory");
      }
      __syncwarp();
      cluster_arrive_relaxed();
      asm volatile("bar.arrive 4, 128;" ::: "memory");
      DBG(1);
      TILES();
      expect_w(bar(B_DIR), 2 * UNIT_BYTES);
      tma3_w(sl + 3 * STAGE_BYTES, &maps.m[M_D], bar(B_DIR), 0, 0, fta * 4);
      const int ca = TR1 && !big ? (TA - TC) * 128 : 0, cb = TR2 && big ? (TB - TD) * 128 : 0;
      const CUtensorMap *ma = &maps.m[M_XA + (ca ? rank : 0)], *mb = &maps.m[M_XB + (cb ? rank : 0)];
      expect_w(bar(B_FULL), X_BYTES - ca);
      cluster_wait();
      tma_mc_w(sl + rank * (X_BYTES / 2), ma, bar(B_FULL), 0, toka + rank * (TA / 2));
      DBG(2);
      expect_w(bar(B_LAST), SLAB_BYTES);
      if (XPE) {
        wait_until(t0, XP0);
        const uint8_t* a = xg + (((blockIdx.x & 127) * 16 + (lane >> 1)) * (K_ * 2) + (lane & 1) * 64);
        if (XPE & 1) asm volatile("prefetch.global.L2 [%0+128];" ::"l"(a));
        if (XPE & 2) asm volatile("prefetch.global.L2 [%0+256];" ::"l"(a));
        if (XPE & 4) asm volatile("prefetch.global.L2 [%0+384];" ::"l"(a));
      }
      if (!NX) wait_exact(t0, XT0);
#pragma unroll
      for (int n = 1; n <= NX; n++) {
        expect_w(bar(B_FULL + n), SLAB_BYTES);
        expect_w(bar(B_X * n), X_BYTES - ca);
        if ((WF >> n) & 1) {
          wait_exact(t0, n == 1 ? G0 : n == 2 ? G1 : G2);
          bulk_w(sl + (n - 1) * STAGE_BYTES + X_BYTES, gp + (fta * KBLKS + n - 1) * SLAB_BYTES, SLAB_BYTES, bar(B_FULL + n));
        }
        if (n == 3) mbar_wait(bar(B_EMPTY + 3), 0, bud);
        wait_exact(t0, n == 1 ? XT0 : n == 2 ? XT2 : XT3);
        tma_mc_w(sl + n * STAGE_BYTES + rank * (X_BYTES / 2), ma, bar(B_X * n), n * BK, toka + rank * (TA / 2));
        DBG(2 + n);
        if (XPD && n >= XPS) {
          const uint8_t* a = xg + (((blockIdx.x & 127) * 16 + (lane >> 1)) * (K_ * 2) + (lane & 1) * 64 + (n + XPD) * 128);
          asm volatile("prefetch.global.L2 [%0];" ::"l"(a));
        }
        if (!((WF >> n) & 1)) {
          wait_exact(t0, n == 1 ? G0 : n == 2 ? G1 : G2);
          bulk_w(sl + (n - 1) * STAGE_BYTES + X_BYTES, gp + (fta * KBLKS + n - 1) * SLAB_BYTES, SLAB_BYTES, bar(B_FULL + n));
        }
      }
#define PT(a)
#pragma unroll 1
      for (int n = NX + 1; n < 2 * KBLKS - 4; n++) {
        const int stage = n & 3;
        const bool first = n < KBLKS;
        const int rows = rank * (first ? TA / 2 : TB / 2);
        if (EXF) expect_w(bar(B_FULL + stage), STAGE_BYTES - (first ? ca : cb));
        mbar_wait(bar(B_EMPTY + stage), ((n - 3) >> 2) & 1, bud);
        PT(pe);
        if (!EXF) expect_w(bar(B_FULL + stage), STAGE_BYTES - (first ? ca : cb));
        tma_mc_w(sl + stage * STAGE_BYTES + rows * 128, first ? ma : mb, bar(B_FULL + stage),
                 (n & (KBLKS - 1)) * BK, (first ? toka : tokb) + rows);
        PT(px);
        if (XPD && n >= XPS && n < KBLKS - XPD) {
          const uint8_t* a = xg + (((blockIdx.x & 127) * 16 + (lane >> 1)) * (K_ * 2) + (lane & 1) * 64 + (n + XPD) * 128);
          asm volatile("prefetch.global.L2 [%0];" ::"l"(a));
          if (!XPW) asm volatile("prefetch.global.L2 [%0+32];" ::"l"(a));
        }
        if (n <= KBLKS) {
          wait_exact(t0, 32 * prmt((uint32_t)GATES, (uint32_t)(GATES >> 32), min(n, 7)));
          bulk_w(sl + ((n - 1) & 3) * STAGE_BYTES + X_BYTES, gp + (fta * KBLKS + n - 1) * SLAB_BYTES, SLAB_BYTES, bar(B_FULL + (n & 19)));
        }
        if (WP && n == 13) asm volatile("bar.arrive 0, 64;" ::: "memory");
        if (WP) continue;
        if (n == PN) wait_count(count + 32 * (1 + ((lds32(sl + OFF_EPOCH) & 256) ? 48 : 0) + 4 * ftb), bud);
        if (first) continue;
        if (n == KBLKS + 4 || n == KBLKS + 8) asm volatile("bar.sync %0, 64;" ::"r"(n & 8) : "memory");
        tma_w(sl + stage * STAGE_BYTES + TB * 128, &maps.m[W128 ? M_W2 : M_W], bar(B_FULL + stage), (n - KBLKS) * BK, ftb * BF);
        if (!W128) tma_w(sl + stage * STAGE_BYTES + TB * 128 + 8192, &maps.m[M_W], bar(B_FULL + stage), (n - KBLKS) * BK, ftb * BF + 64);
        PT(pw);
      }
      const CUtensorMap *mx = &maps.m[M_XB], *mw = &maps.m[M_W];
      DBG(220);
      expect_w(bar(B_RDY), 16384);
      expect_w(bar(B_W), 16384);
      asm volatile("bar.sync 15, %0;" ::"n"(WP ? 128 : 96) : "memory");
      tma3_w(sl + OFF_STG + 49152, mw, bar(B_W), 0, ftb * BF, 14);
      expect_w(bar(B_FULL), STAGE_BYTES);
      uint32_t xd = sl + rank * 12288, xb = bar(B_FULL), xk = (12 + rank) * BK, xt = tokb, wd = sl + 24576, wb = xb, wf = ftb * BF, wk = 12;
#pragma unroll 1
      for (int i = 0; i < 4; i++) {
        wait_tma_mc_w(bar(B_EMPTY) + 8 * i, i == 3, bud, xd, mx, xb, xk, xt);
        if (i < 2) tma3_w(wd, mw, wb, 0, wf, wk);
        wf = ftb * BF + 64;
        if (i == 0) tma3_w(sl + OFF_STG + 16384, mw, bar(B_RDY), 0, wf, 12);
        if (i < 3) expect_w(bar(B_FULL + 1) + 8 * i, i == 2 ? 49152 - 4 * cb : 24576 - 8192 * i);
        xd += STAGE_BYTES; wd += STAGE_BYTES; xk ^= 2 * BK; wk = 14; wb = bar(B_FULL + 2);
        if (i) xb = bar(B_FULL + 3), xt = tokb + TB / 2, mx = &maps.m[cb ? M_XD : M_XB];
        else xb = bar(B_FULL + 1);
      }
      asm volatile(ELECT "@p red.relaxed.gpu.global.add.u32 [%0], %1;\n}\n" ::"l"(count), "r"(blockIdx.x < 2 * NUM_CTAS - 256 ? 1 : 2) : "memory");
    } else {
      const int p = warp - 1;
      uint32_t ep;
      asm volatile("ld.relaxed.gpu.global.u32 %0, [%1];" : "=r"(ep) : "l"(count) : "memory");
      cluster_arrive_relaxed();
      prefetch_map(&maps.m[p + (TR1 && p == 2 && (te & 15) >= 12 ? rank : 0)]);
      asm volatile("prefetch.global.L2 [%0];" ::"l"(xg + (((blockIdx.x * 16 + p * 8 + (lane >> 2)) & (M_ - 1)) * (K_ * 2) + (lane & 3) * 32)));
      const uint32_t so = OFF_STG + p * UNIT_BYTES;
      const uint32_t ua = sl + so + (lane & 3) * 256 + (((lane >> 2) ^ (2 * (lane & 3))) << 4);
      asm volatile("bar.sync 4, 128;" ::: "memory");
      if (!EPW && p == 2) {
        sts32(sl + OFF_EPOCH, ep);
        asm volatile("bar.arrive 1, 288;" ::: "memory");
      }
      int r = blockIdx.x, u = 128 + U0(r, p);
      const uint32_t jobv = maps.jobs[3 * r + p + (tid >> 10)];
      uint32_t job;
      uint32_t ph = 0, odd;
#pragma unroll 1
      do {
        wait_until(t0, D0 + (u - 128) * PU / 4);
        expect_w(bar(B_SLOT + p), UNIT_BYTES);
        tma_w(sl + so, &maps.m[M_Q], bar(B_SLOT + p), (u & 63) * 32, (u & ~63) + 32);
        DBG(16 + 8 * p + 2 * (r / NUM_CTAS));
        uint8_t* dst = gp + (((((u & 63) >> 2) * KBLKS + (u >> 6)) * 4 + (u & 3)) * 2048 + (lane >> 2) * 256 + (lane & 3) * 16);
        mbar_wait(bar(B_SLOT + p), ph, bud);
        asm volatile("and.b32 %0, %1, 256;" : "=r"(odd) : "r"(ep));
        DBG(184 + 4 * p + r / NUM_CTAS);
        uint32_t w[4][4];
#pragma unroll
        for (int b = 0; b < 4; b++) {
          uint32_t v[4][4];
          lds128(v[0], ua + b * 2048);
          lds128(v[1], (ua ^ 16) + b * 2048 + 128);
          lds128(v[2], ua + b * 2048 + 1024);
          lds128(v[3], (ua ^ 16) + b * 2048 + 1024 + 128);
#pragma unroll
          for (int j = 0; j < 4; j++) w[j][b] = make_word(v[0][j], v[1][j], v[2][j], v[3][j], word_key(odd));
        }
        st_words<0>(dst, w[0]); st_words<64>(dst, w[1]); st_words<128>(dst, w[2]); st_words<192>(dst, w[3]);
        __syncwarp();
        DBG(17 + 8 * p + 2 * (r / NUM_CTAS));
        ph ^= 1;
        r += NUM_CTAS;
        job = __shfl_sync(0xffffffffu, jobv, 0);
        u = ph ? u + 3 * NUM_CTAS : job & 2047;
      } while (u < 1024);
      const int l = (job >> 11) & 511;
      const int ls = (l * 1366) >> 16, cg = l - 48 * ls;
      unsigned int* cnt = count + (32 + 6 * __shfl_sync(0xffffffffu, odd, 0));
      prefetch_map(&maps.m[M_XB + p]);
      prefetch_map(&maps.m[M_Q2]);
      if (l < 384) {
        uint32_t e[8];
        const __nv_bfloat16* s = maps.lut + ((lane & 15) * N_ + 2048 + cg * 32 + (lane & 16));
        asm volatile("ld.global.nc.v4.u32 {%0, %1, %2, %3}, [%4];" : "=r"(e[0]), "=r"(e[1]), "=r"(e[2]), "=r"(e[3]) : "l"(s));
        asm volatile("ld.global.nc.v4.u32 {%0, %1, %2, %3}, [%4+16];" : "=r"(e[4]), "=r"(e[5]), "=r"(e[6]), "=r"(e[7]) : "l"(s));
        wait_until(t0, (job >> 20) * 8);
        expect_w(bar(B_SLOT + p), 2 * UNIT_BYTES);
        tma3_w(sl + so, &maps.m[M_Q2], bar(B_SLOT + p), 2048 + cg * 32, ls * 16, 0);
        tma3_w(sl + so + 32768, &maps.m[M_Q2], bar(B_SLOT + p), 2048 + cg * 32, ls * 16, 4);
        DBG(22 + 8 * p);
        uint32_t tab = sl + OFF_TAB + p * 1536 + (SHF ? lane * 32 : (lane >> 4) * 644);
        if (SHF) {
          sts128(tab, e);
          sts128(tab + 16, e + 4);
        } else {
#pragma unroll
          for (int i = 0; i < 8; i++) sts32(tab + (lane & 15) * 40 + 4 * i, e[i]);
          __syncwarp();
        }
        uint8_t* dst = gp + (W_OFF + cg * 65536 + ls * 256 + (lane >> 4) * 32768 + (lane & 15) * 16);
        const uint32_t src = sl + so + (lane & 15) * 128 + ((((lane >> 2) & 4) ^ (lane & 7)) << 4);
        mbar_wait(bar(B_SLOT + p), ph, bud);
#pragma unroll 1
        for (int c = 0; c < 64; c += 16, tab += 8, dst += 8192) {
          uint32_t v[8][4];
#pragma unroll
          for (int i = 0; i < 8; i++) lds128(v[i], (src ^ c) + (i & 3) * 2048 + (i >> 2) * 32768);
          if (SHF) {
            asm volatile("ld.shared.v2.u32 {%0, %1}, [%2];" : "=r"(e[0]), "=r"(e[1]) : "r"(tab) : "memory");
            convert_shfl<0>(v, e[0], dst);
            convert_shfl<1>(v, e[0], dst);
            convert_shfl<2>(v, e[1], dst);
            convert_shfl<3>(v, e[1], dst);
          } else {
          convert_col<0>(v, tab, dst);
          convert_col<1>(v, tab, dst);
          convert_col<2>(v, tab, dst);
          convert_col<3>(v, tab, dst);
          }
        }
        __syncwarp();
        DBG(23 + 8 * p);
      }
      arrive_w(bar(B_LAST));
      if (l < 384)
        asm volatile(ELECT "@p fence.proxy.async.global;\n@p red.release.gpu.global.add.u32 [%0], %1;\n}\n"
                     ::"l"(cnt + 32 * ((cg & ~3) + min(ls >> 1, 2))), "r"(ls < 4 ? 8 : 4) : "memory");
      cluster_wait();
      TILES();
      const int q = WP ? (RM >> (p + p)) & 3 : p;
      prefetch_map(&maps.m[M_W - q]);
      prefetch_map(&maps.m[M_W2]);
      if (q > 0) {
        asm volatile("bar.sync %0, 160;" ::"r"(12 + q) : "memory");
        if (FEN) asm volatile("fence.proxy.async.shared::cta;" ::: "memory");
        uint32_t t1 = clock();
#pragma unroll 1
        for (int i = 0; i < TA; i += OB, t1 += PC * OB / 32) {
          wait_until(t1, 0);
          const int rr = min(i ^ 128, (big ? TA : TC) - OB);
          if (i == 128) {
            bulk_wait_read();
            asm volatile("bar.arrive 15, %0;" ::"n"(WP ? 128 : 96) : "memory");
          }
          store_w(&maps.m[M_O32], sl + OFF_STG + (q - 1) * 32768 + rr * 128, fta * BF + 64 * (q - 1), toka + rr);
        }
        bulk_wait_read();
        DBG(227 + q);
        asm volatile("bar.arrive %0, 160;" ::"r"(12 + q) : "memory");
        const uint32_t sg = sl + OFF_STG + (q - 1) * 32768;
        const int c0 = 2048 + ftb * BF + 64 * (q - 1);
        uint32_t ids = q == 1 ? 0x0d126 : 0x8e437;
        const CUtensorMap* mo = &maps.m[M_O48];
        uint32_t os = sg + 48 * 128, ot = tokb + 48;
#pragma unroll 1
        for (int k = 0; k < 5; k++) {
          asm volatile("bar.sync %0, 160;\nfence.proxy.async.shared::cta;\n"
                       ELECT "@p cp.async.bulk.tensor.2d.global.shared::cta.bulk_group [%1, {%3, %4}], [%2];\n}\n"
                       "cp.async.bulk.commit_group;"
                       ::"r"((ids & 15) | ((os + ot + k + (uint32_t)((uint64_t)mo >> 32)) & (bud >> 31))), "l"((uint64_t)mo), "r"(os), "r"(c0), "r"(ot) : "memory");
          const int r = k ? 64 + 32 * k : 0;
          ids >>= 4; os = sg + r * 128; ot = tokb + r;
          if (k == 1 || (k == 3 && big)) mo--;
        }
        bulk_wait_read();
      } else {
        if (blockIdx.x < 48) count[32 * (50 + blockIdx.x) - (cnt - count)] = 0;
        if (WP) {
          asm volatile("bar.sync 0, 64;" ::: "memory");
#pragma unroll 1
          for (int n = 0; n < KBLKS - 4; n++) {
            if ((n & 3) == 0) wait_count(cnt + 32 * 4 * ftb + 8 * n, bud);
            if (n == 8) asm volatile("bar.arrive 15, 128;" ::: "memory");
            mbar_wait(bar(B_EMPTY + (n & 3)), ((n + 13) >> 2) & 1, bud);
            tma_w(sl + (n & 3) * STAGE_BYTES + TB * 128, &maps.m[W128 ? M_W2 : M_W], bar(B_FULL + (n & 3)), n * BK, ftb * BF);
            if (!W128) tma_w(sl + (n & 3) * STAGE_BYTES + TB * 128 + 8192, &maps.m[M_W], bar(B_FULL + (n & 3)), n * BK, ftb * BF + 64);
          }
        } else {
#pragma unroll 1
        for (int i = 1; i < 3; i++) {
          wait_count(cnt + 32 * (4 * ftb + i), bud);
          asm volatile("bar.arrive %0, 64;" ::"r"(8 * i - 8) : "memory");
        }
        }
      }
    }
    asm volatile("exit;");
  }
  const int cw = wg - 1;
  TILES();
  cluster_arrive_relaxed();
  if (warp >= 2) {
    ld_lut<0>(cf, lut + (fta * BF + 4 * (lane & 3) * N_ + 64 * cw + 32 * (warp & 1) + (lane & 16) + ((lane >> 1) & 6)));
  } else if (cw) {
    spin_until(t0, S1D);
    ld_codes(cf, src);
  } else if (EPW) {
    sts32(sl + OFF_EPOCH, ep0);
    asm volatile("bar.arrive 1, 256;" ::: "memory");
  }
  if (EPW) {
    if (w12 >= 6) asm volatile("bar.sync 1, 256;" ::: "memory");
  } else asm volatile("bar.sync 1, 288;" ::: "memory");
  const uint32_t odd = lds32(sl + OFF_EPOCH) & 256;
  DBG(40 + w12);
  if (warp >= 2) store_planes(sl + OFF_PL + cw * 32768 + (warp & 1) * 1024 + (lane & 28) * 32 + (lane & 3) * 16, cf);
  else {
    uint8_t* dst = gp + (((blockIdx.x & 120) * 2 + cw) * SLAB_BYTES + (blockIdx.x & 7) * 1024 + (tid & 63) * 16);
    const uint32_t tb = sl + OFF_STG + 61440 + cw * 1024;
#pragma unroll
    for (int j = 0; j < 4; j++)
      sts32(tb + (lane & 3) * 256 + j * 64 + (lane & 12) * 4 + ((tid >> 2) & 12), make_word(cf[j], cf[4 + j], cf[8 + j], cf[12 + j], word_key(odd)));
    asm volatile("bar.sync %0, 64;" ::"r"(6 + cw) : "memory");
    lds128(cf, tb + (tid & 63) * 16);
    st_words<0>(dst, cf);
  }
  DBG(52 + w12);
  asm volatile("setmaxnreg.inc.sync.aligned.u32 216;");
  uint32_t rel = (tid & 127) < 2 ? mapa(bar(B_EMPTY), lane) : 0u;
  uint32_t tg = (w12 - 4) * 1024 + lane * 16;
  uint32_t tw = sl + X_BYTES + tg;
  const uint8_t* gt = gp + (tg + fta * KBLKS * SLAB_BYTES);
  uint32_t tag = (1u << 28) - (odd << 19), sc = 0x3c00 + 8 * odd;
  asm volatile("" : "+r"(tw), "+l"(gt), "+r"(rel), "+r"(tag), "+r"(sc));
  Planes pl;
  uint32_t A[16], P[8];
  float acc[TA / 2];
  DBG(64 + cw);
  if (PLF) {
  asm volatile("bar.sync %0, 128;" ::"r"(2 + cw) : "memory");
#pragma unroll
  for (int k = 0; k < 4; k++) lds128(pl.v[k], sl + OFF_PL + cw * 32768 + (tid & 124) * 16 + 16 * k);
  }
  {
    const uint32_t td = sl + 3 * STAGE_BYTES - 8192 + (w12 >> 1) * 4096 + (lane & 3) * 256 + ((((tid >> 3) & 4) ^ (lane >> 4) ^ (2 * (lane & 3))) << 4) + (lane & 12);
    mbar_wait(bar(B_DIR), 0, bud);
    DBG(88 + cw);
#pragma unroll
    for (int k = 0; k < 4; k++) {
      const uint32_t a = (td ^ ((k & 2) << 4)) + (k & 1) * 2048;
      P[2 + (k & 1) + 2 * (k & 2)] = make_word(lds32(a), lds32((a ^ 16) + 128), lds32(a + 1024), lds32((a ^ 16) + 1152), word_key(odd));
    }
  }
  if (!PLF) {
  asm volatile("bar.sync %0, 128;" ::"r"(2 + cw) : "memory");
#pragma unroll
  for (int k = 0; k < 4; k++) lds128(pl.v[k], sl + OFF_PL + cw * 32768 + (tid & 124) * 16 + 16 * k);
  }
  if (!NX) mbar_wait(bar(B_FULL), 0, bud);
  DBG(66 + cw);
#define CNT(i)
  auto rest = [&](auto ty) {
  constexpr bool big = decltype(ty)::v;
  auto tile1 = [&](auto nh) {
    uint32_t fb = bar(B_LAST) - 128 * cw, fm = 0x98 + 128 * cw;
    asm volatile("" : "+r"(fb), "+r"(fm));
    uint64_t d = desc1;
    uint32_t m = 128, pa = 0;
#pragma unroll 1
    do {
      m += 8;
      uint32_t fa;
      asm volatile("lop3.b32 %0, %1, %2, %3, 0x6a;" : "=r"(fa) : "r"(m), "r"(fm), "r"(fb));
      const uint32_t o = m & 24, par = PAR ? m >> 5 : (m >> 5) & 1;
      bool ok;
#pragma unroll
      for (int b = 0; b < 4; b++) {
        if (b == 1 && !ok) mbar_wait(fa, par, bud);
        if (b == 2) {
#pragma unroll 1
          while (__builtin_expect(!__all_sync(0xffffffffu, words_ok(P, tag)), 0)) {
            if ((bud += 16) >= 0x100000) break;
            asm volatile("{\n.reg .b64 a, l, h;\n.reg .b128 t, u;\nmad.wide.u32 a, %8, 1024, %9;\n"
                         "ld.relaxed.gpu.global.b128 t, [a+-139264];\nld.relaxed.gpu.global.b128 u, [a+-138752];\n"
                         "mov.b128 {l, h}, t;\nmov.b64 {%0, %1}, l;\nmov.b64 {%2, %3}, h;\n"
                         "mov.b128 {l, h}, u;\nmov.b64 {%4, %5}, l;\nmov.b64 {%6, %7}, h;\n}\n"
                         : "=r"(P[0]), "=r"(P[1]), "=r"(P[2]), "=r"(P[3]), "=r"(P[4]), "=r"(P[5]), "=r"(P[6]), "=r"(P[7]) : "r"(m), "l"(gt) : "memory");
          }
        }
        CNT(2 * b);
        lookup4(pl, 0, P[b ^ 2], sc, A[4 * b], A[4 * b + 2]);
        lookup4(pl, 1, P[4 + (b ^ 2)], sc, A[4 * b + 1], A[4 * b + 3]);
        if (b == 1) {
          lds128(P, tw + pa);
          lds128(P + 4, tw + pa + 512);
        }
        if (b == 1) asm volatile("mul.lo.u32 %0, %1, %2;" : "=r"(pa) : "r"(o), "n"(STAGE_BYTES / 8));
        if (((WD >> (4 * b)) & 3) == 1) wgmma_wait<1>();
        if (((WD >> (4 * b)) & 3) == 2) wgmma_wait<2>();
        if (b == RB) mbar_arrive_remote_if(rel + (o ^ 16), rel);
        if (b == 0) ok = mbar_test(fa, par);
        if (NX && b == 0 && m < 144 + 8 * NX) {
          uint32_t xa;
          asm volatile("mad.lo.u32 %0, %1, %2, %3;" : "=r"(xa) : "r"(m), "n"(B_X), "r"(bar(B_FULL) - 136 * B_X));
          mbar_wait(xa, 0, bud);
        }
        CNT(2 * b + 1);
        wgmma_fence();
        if (b) wgmma_rl<decltype(nh)::v>(acc, A + 4 * b, d + 2 * b + 2);
        else wgmma_rp<decltype(nh)::v>(acc, A, d + 2, m > 136);
        wgmma_commit();
      }
      asm volatile("mov.b64 %0, {%1, %2};" : "=l"(d) : "r"(UD - 2 + (pa >> 4)), "r"((uint32_t)(d >> 32)));
    } while (m < 256);
  };
  tile1(IC<big ? TA : TC>());
  if (cw != 1) mbar_arrive(bar(B_SK));
  const uint32_t stg = sl + OFF_STG + cw * 32768;
  const uint32_t so8 = stg + ((lane & 7) + ((lane >> 4) << 3)) * 128 + (((2 * warp + ((lane >> 3) & 1)) ^ (lane & 7)) << 4);
  DBG(212 + cw);
  mbar_wait(bar(B_FULL), 0, bud);
  DBG(214 + cw);
  DBG(216 + cw);
  const uint64_t ub = maps.desc[3 * big], ua = ub + (TB * 8 + cw * 512);
  const uint64_t vb = maps.desc[3 * big + 1], va = vb + (TB * 8 + cw * 512), uc = maps.desc[3 * big + 2];
  wgmma_wait<0>();
  mbar_arrive_remote_if(rel + 24, rel);
  fence_regs(acc);
  DBGR(0, 68 + cw);
#define PKT(i)
  auto start2 = [&](auto nt) {
    uint32_t o[64];
#pragma unroll
    for (int k = 0; k < 48; k++) o[k] = pack_bf16(acc[2 * k], acc[2 * k + 1]);
#pragma unroll
    for (int k = 0; k < 48; k++) asm volatile("" : "+r"(o[k]) :: "memory");
    DBG(92 + cw);
    PKT(0);
    wgmma_fence();
#pragma unroll
    for (int b = 0; b < 4 * NP; b++) {
      const int so = (b >> 2) * (STAGE_BYTES / 16) + 2 * (b & 3);
      if (b && !(b & 3)) mbar_wait(bar(B_FULL + (b >> 2)), 0, bud);
      wgmma_ss<decltype(nt)::v>(acc, ua + so, ub + so, b != 0);
      if ((b & 3) == 3 || (b && !(b & 3))) wgmma_commit();
      if (b == 0) {
#pragma unroll
        for (int k = 48; k < 64; k++) o[k] = pack_bf16(acc[2 * k], acc[2 * k + 1]);
      }
      if (b && !(b & 3)) {
        wgmma_wait<1>();
        mbar_arrive_remote_if(rel + 2 * b - 8, rel);
      }
#pragma unroll
      for (int j = 0; j < 16; j++)
        if (((SMK >> (4 * j)) & 15) == b) stmatrix_x4_t(so8 + (j ^ SJ) * 2048, o[4 * (j ^ SJ)], o[4 * (j ^ SJ) + 1], o[4 * (j ^ SJ) + 2], o[4 * (j ^ SJ) + 3]);
      PKT(b + 1);
    }
  };
  start2(IC<big ? TD : TB>());
  if (!FEN) asm volatile("fence.proxy.async.shared::cta;" ::: "memory");
  asm volatile("bar.arrive %0, 160;" ::"r"(13 + cw) : "memory");
  cluster_wait();
  DBG(70 + cw);
  uint32_t W[64];
  const uint32_t wa = sl + (warp * 16 + (lane & 15)) * 128 + (((lane >> 4) ^ (lane & 7)) << 4);
  const uint32_t w0 = wa + (cw ? OFF_STG + 16384 : 24576), w2 = wa + (cw ? STAGE_BYTES + 24576 : OFF_STG + 49152);
  auto tile2 = [&](auto nt) {
    auto step = [&](int n, bool last) {
      const uint32_t so = (n & 3) * (STAGE_BYTES / 16);
      mbar_wait_fast(bar(B_FULL) + 8 * (n & 3), (n >> 2) & 1, bud);
      if (last && EW == 0) mbar_wait(bar(B_W), 0, bud);
      wgmma_fence();
      wgmma_ss<decltype(nt)::v>(acc, va + so, vb + so, 1);
      wgmma_commit();
      if (last) {
        if (EW == 1) mbar_wait(bar(B_W), 0, bud);
#pragma unroll
        for (int b = 8; b < U0A; b++) {
          if (PEEL) ldmatrix_x4_if(W + 4 * b, (w2 ^ ((b & 3) << 5)) + ((b >> 2) & 1) * 8192, cw);
          else ldmatrix_x4(W + 4 * b, (w2 ^ ((b & 3) << 5)) + ((b >> 2) & 1) * 8192);
        }
      }
      wgmma_wait<1>();
      mbar_arrive_remote_if(rel + 8 * ((n - 1) & 3), rel);
#pragma unroll
      for (int b = 1; b < 4; b++) wgmma_ss<decltype(nt)::v>(acc, va + so + 2 * b, vb + so + 2 * b, 1);
      wgmma_commit();
    };
#pragma unroll 1
    for (int n = NP; n < KBLKS - 4; n++) step(n, n == KBLKS - 5 + 8 * cw);
  };
  tile2(IC<big ? TD : TB>());
  float c2[TB / 2];
  DBGR(1, 72 + cw);
  auto ldw = [&](int b) { ldmatrix_x4(W + 4 * b, ((b & 8 ? w2 : w0) ^ ((b & 3) << 5)) + ((b >> 2) & 1) * 8192); };
  const uint32_t b2 = bar(B_FULL + 1 + cw);
  mbar_wait(bar(cw ? B_RDY : B_FULL), 1, bud);
  if (cw) DBG(226);
#pragma unroll
  for (int b = 0; b < PF; b++) {
    ldw(b);
  }
  bool ok = false;
  wgmma_wait<0>();
  mbar_arrive_remote_if(rel + 24, rel);
  if (PKI == -2) ok = mbar_test(b2, 1);
  if (cw) {
    mbar_wait(b2, 1, bud);
    DBG(227);
#pragma unroll
    for (int b = 8; b < UA; b++) ldw(b);
  }
#pragma unroll
  for (int k = 0; k < TB / 2; k++) asm volatile("mov.b32 %0, %1;" : "=f"(c2[k]) : "f"(acc[k]) : "memory");
#pragma unroll
  for (int h = 0; h < 2 - T3; h++) {
    constexpr int L = 48;
    if (h) mbar_wait(bar(B_FULL + 3), 1, bud);
    if (h || cw) asm volatile("bar.sync %0, 256;" ::"r"(9 + 2 * h + cw) : "memory");
    DBGR(2 + 3 * h, 74 + 6 * h + cw);
    if (h == 0 && PKI == -1) ok = mbar_test(b2, 1);
    auto part = [&](auto nn) {
#pragma unroll
      for (int i = 0; i < 16; i++) {
        if (h ? i >= QD1 && i <= QN1 : i >= QD0 && i <= QN0) {
          if (h) wgmma_wait<QD1 - 1>(); else wgmma_wait<QD0 - 1>();
        }
        if (i == 0 || (h == 0 && ((FM0 >> i) & 1))) wgmma_fence();
        const int off = ((2 * h + (i >> 3)) * STAGE_BYTES + ((i >> 2) & 1) * 12288 + L * 128) / 16 + 2 * (i & 3);
        if constexpr (decltype(nn)::v == TB / 2 - L) wgmma_rl<decltype(nn)::v>(c2 + 48 * h + L / 2, W + 4 * i, uc + off);
        else wgmma_rs<decltype(nn)::v>(c2 + 48 * h + L / 2, W + 4 * i, UD + off, 1);
        if (h == 0 && i < IX) wgmma_rl<L>(c2, W + 4 * i, uc + off - L * 8);
        if (i < (h ? QN1 : QN0) || (!h && i == NA)) wgmma_commit();
        if (h == 0) {
          constexpr int J0 = U0A < UA ? U0A : UA;
#pragma unroll
          for (int e = 0; e < LPS; e++) {
            const int j = (i - LD0) * LPS + J0 + e;
            if (j >= J0 && j < UA) ldmatrix_x4_if(W + 4 * j, (w2 ^ ((j & 3) << 5)) + ((j >> 2) & 1) * 8192, cw);
            else if (j >= J0 && j < U0A) ldmatrix_x4_if(W + 4 * j, (w2 ^ ((j & 3) << 5)) + ((j >> 2) & 1) * 8192, cw ^ 1);
            else if (j >= J0 && j < 16) ldw(j);
          }
          if (i == PKI) ok = mbar_test(b2, 1);
          if (i == WI && !ok) mbar_wait(b2, 1, bud);
        }
      }
      wgmma_commit();
    };
    if (h && big) part(IC<TD - TB / 2 - L>()); else part(IC<TB / 2 - L>());
    const int k0 = h ? K0 : K00 + IX;
    if (h) wgmma_fence();
#pragma unroll
    for (int i = h ? 0 : IX; i < 16; i++) {
      const int off = ((2 * h + (i >> 3)) * STAGE_BYTES + ((i >> 2) & 1) * 12288) / 16 + 2 * (i & 3);
      wgmma_rl<L>(c2 + 48 * h, W + 4 * i, uc + off);
      if (i == k0 - 1) {
        wgmma_commit();
        if (!h) asm volatile("bar.sync %0, 160;" ::"r"(13 + cw) : "memory");
        if (!h) {
          wgmma_wait<2>();
          asm volatile("bar.arrive %0, 256;" ::"r"(10 + cw) : "memory");
        }
        wgmma_wait<1>();
#pragma unroll
        for (int k = L / 2; k < 48; k++) asm volatile("" : "+f"(c2[48 * h + k]) :: "memory");
        if (h == TCH) DBGR(8, 218 + cw);
      }
      const int j = i - k0 + 1 + L / 16;
      if (i >= k0 - 1 && j < 6) stage_part<1>(c2 + 48 * h + 8 * j, so8 + 16 * 128 * (6 * h + j));
      if (j == 5) asm volatile("bar.arrive %0, 160;" ::"r"(h ? 1 + 3 * cw : 6 + cw) : "memory");
    }
    wgmma_commit();
    if (h) asm volatile("{\n.reg .pred p;\nsetp.eq.u32 p, %0, 0;\n@p bar.arrive 12, 256;\n}\n" ::"r"(cw) : "memory");
    if (h == TCH) DBGR(9, 230 + cw);
    wgmma_wait<0>();
#pragma unroll
    for (int k = 0; k < L / 2; k++) asm volatile("" : "+f"(c2[48 * h + k]) :: "memory");
    DBGR(3 + 3 * h, 76 + 6 * h + cw);
    stage_part<L / 16>(c2 + 48 * h, so8 + 96 * 128 * h);
    asm volatile("bar.arrive %0, 160;" ::"r"(h ? 8 * cw : 2 + cw) : "memory");
    DBGR(4 + 3 * h, 78 + 6 * h + cw);
  }
  if (T3) {
    mbar_wait(bar(B_FULL + 3), 1, bud);
    asm volatile("bar.sync %0, 256;" ::"r"(11 + cw) : "memory");
    DBGR(5, 80 + cw);
    auto part = [&](auto nn, auto pp) {
      constexpr int p = decltype(pp)::v;
      constexpr int kk = p == 2 ? K4 : K3;
      float* c = c2 + 48 + 16 * p;
      wgmma_fence();
#pragma unroll
      for (int i = 0; i < 16; i++) {
        if (p == 0 && i >= QD3 && i <= QN3) wgmma_wait<QD3 - 1>();
        const int off = ((2 + (i >> 3)) * STAGE_BYTES + ((i >> 2) & 1) * 12288 + 32 * p * 128) / 16 + 2 * (i & 3);
        if constexpr (p == 2 && decltype(nn)::v == R24) wgmma_rs<decltype(nn)::v>(c, W + 4 * i, UD + off, 1);
        else wgmma_rl<decltype(nn)::v>(c, W + 4 * i, uc + off);
        if (p == 0 && i < QN3) wgmma_commit();
        if (p == 2 && i == HI) asm volatile("{\n.reg .pred p;\nsetp.eq.u32 p, %0, 0;\n@p bar.arrive 12, 256;\n}\n" ::"r"(cw) : "memory");
        if (p && i == kk - 1) {
          wgmma_commit();
          wgmma_wait<1>();
#pragma unroll
          for (int k = -16; k < 0; k++) asm volatile("" : "+f"(c[k]) :: "memory");
          if (TCH && p == TCH) DBGR(8, 218 + cw);
        }
        const int j = i - kk + 1;
        if (p && (j == 0 || j == 1)) stage_part<1>(c - 16 + 8 * j, so8 + (64 + 32 * p + 16 * j) * 128);
        if (p && j == 1 + AD) asm volatile("bar.arrive %0, 160;" ::"r"(p == 1 ? 1 + 3 * cw : 13 + cw) : "memory");
      }
      wgmma_commit();
    };
    part(IC<32>(), IC<0>());
    part(IC<32>(), IC<1>());
    part(IC<big ? 24 : 32>(), IC<2>());
    if (HI == 16) asm volatile("{\n.reg .pred p;\nsetp.eq.u32 p, %0, 0;\n@p bar.arrive 12, 256;\n}\n" ::"r"(cw) : "memory");
    if (TCH) DBGR(9, 230 + cw);
    wgmma_wait<0>();
#pragma unroll
    for (int k = 80; k < 96; k++) asm volatile("" : "+f"(c2[k]) :: "memory");
    DBGR(6, 82 + cw);
    stage_part<2>(c2 + 80, so8 + 160 * 128);
    asm volatile("bar.arrive %0, 160;" ::"r"(8 * cw) : "memory");
    DBGR(7, 84 + cw);
  }
  if (big && PADN) {
    asm volatile("{\n.reg .pred p;\nsetp.ge.s32 p, %0, 0;\n@p exit;\n}\n" ::"r"(bud) : "memory");
#pragma unroll
    for (int i = 0; i < PADN; i++) asm volatile("membar.cta;" ::: "memory");
  }
  };
  if (!big) rest(IC<0>()); else rest(IC<1>());
}

typedef CUresult (*EncodeFn)(CUtensorMap*, CUtensorMapDataType, cuuint32_t, void*, const cuuint64_t*, const cuuint64_t*,
                             const cuuint32_t*, const cuuint32_t*, CUtensorMapInterleave, CUtensorMapSwizzle,
                             CUtensorMapL2promotion, CUtensorMapFloatOOBfill);

}

extern "C" void kernel_launch(void* const* d_in, const int* in_sizes, int n_in, void* d_out, int out_size) {
  const __nv_bfloat16* x = (const __nv_bfloat16*)d_in[0];
  const int* qw = (const int*)d_in[1];
  const __nv_bfloat16* lut = (const __nv_bfloat16*)d_in[2];

  static EncodeFn enc = nullptr;
  static unsigned int* count = nullptr;
  static uint8_t* gp = nullptr;
  if (!enc) {
    cudaDriverEntryPointQueryResult q;
    void* fn = nullptr;
    cudaGetDriverEntryPoint("cuTensorMapEncodeTiled", &fn, cudaEnableDefault, &q);
    enc = (EncodeFn)fn;
    cudaGetSymbolAddress((void**)&count, g_count);
    cudaGetSymbolAddress((void**)&gp, g_p);
    cudaFuncSetAttribute(fused_kernel, cudaFuncAttributeMaxDynamicSharedMemorySize, SMEM_BYTES);
  }
  Maps maps;
  const cuuint32_t es[3] = {1, 1, 1};
  auto map2 = [&](int i, CUtensorMapDataType t, const void* p, int d0, int d1, int bytes, int b0, int b1, CUtensorMapL2promotion pr) {
    cuuint64_t dims[2] = {(cuuint64_t)d0, (cuuint64_t)d1};
    cuuint64_t strides[1] = {(cuuint64_t)d0 * bytes};
    cuuint32_t box[2] = {(cuuint32_t)b0, (cuuint32_t)b1};
    enc(&maps.m[i], t, 2, (void*)p, dims, strides, box, es, CU_TENSOR_MAP_INTERLEAVE_NONE, CU_TENSOR_MAP_SWIZZLE_128B, pr, CU_TENSOR_MAP_FLOAT_OOB_FILL_NONE);
  };
  map2(M_XA, CU_TENSOR_MAP_DATA_TYPE_BFLOAT16, x, K_, M_, 2, BK, TA / 2, XPROM);
  map2(M_XC, CU_TENSOR_MAP_DATA_TYPE_BFLOAT16, x, K_, M_, 2, BK, TC - TA / 2, XPROM);
  map2(M_XD, CU_TENSOR_MAP_DATA_TYPE_BFLOAT16, x, K_, M_, 2, BK, TD - TB / 2, XPROM);
  map2(M_XB, CU_TENSOR_MAP_DATA_TYPE_BFLOAT16, x, K_, M_, 2, BK, TB / 2, XPROM);
  map2(M_O24, CU_TENSOR_MAP_DATA_TYPE_BFLOAT16, d_out, N_, M_, 2, 64, 24, CU_TENSOR_MAP_L2_PROMOTION_NONE);
  map2(M_O32, CU_TENSOR_MAP_DATA_TYPE_BFLOAT16, d_out, N_, M_, 2, 64, OB, CU_TENSOR_MAP_L2_PROMOTION_NONE);
  map2(M_O48, CU_TENSOR_MAP_DATA_TYPE_BFLOAT16, d_out, N_, M_, 2, 64, 48, CU_TENSOR_MAP_L2_PROMOTION_NONE);
  map2(M_Q, CU_TENSOR_MAP_DATA_TYPE_INT32, qw, N_, K_, 4, 32, BK, QPROM);
  {
    cuuint64_t dims[3] = {BK, (cuuint64_t)N_ - 2048, KBLKS};
    cuuint64_t strides[2] = {(cuuint64_t)K_ * 2, BK * 2};
    cuuint32_t box[3] = {BK, 64, 2};
    enc(&maps.m[M_W], CU_TENSOR_MAP_DATA_TYPE_BFLOAT16, 3, (void*)(gp + W_OFF), dims, strides, box, es, CU_TENSOR_MAP_INTERLEAVE_NONE,
        CU_TENSOR_MAP_SWIZZLE_128B, XPROM, CU_TENSOR_MAP_FLOAT_OOB_FILL_NONE);
  }
  map2(M_W2, CU_TENSOR_MAP_DATA_TYPE_BFLOAT16, gp + W_OFF, K_, N_ - 2048, 2, BK, 128, XPROM);
  {
    cuuint64_t dims[3] = {(cuuint64_t)N_, (cuuint64_t)K_ / 8, 8};
    cuuint64_t strides[2] = {(cuuint64_t)N_ * 32, (cuuint64_t)N_ * 4};
    cuuint32_t box[3] = {32, 16, 4};
    enc(&maps.m[M_Q2], CU_TENSOR_MAP_DATA_TYPE_INT32, 3, (void*)qw, dims, strides, box, es, CU_TENSOR_MAP_INTERLEAVE_NONE,
        CU_TENSOR_MAP_SWIZZLE_128B, QPROM, CU_TENSOR_MAP_FLOAT_OOB_FILL_NONE);
  }
  {
    cuuint64_t dims[3] = {32, (cuuint64_t)K_, (cuuint64_t)N_ / 32};
    cuuint64_t strides[2] = {(cuuint64_t)N_ * 4, 128};
    cuuint32_t box[3] = {32, 32, 4};
    enc(&maps.m[M_D], CU_TENSOR_MAP_DATA_TYPE_INT32, 3, (void*)qw, dims, strides, box, es, CU_TENSOR_MAP_INTERLEAVE_NONE,
        CU_TENSOR_MAP_SWIZZLE_128B, QPROM, CU_TENSOR_MAP_FLOAT_OOB_FILL_NONE);
  }
  for (int i = 0; i < 6; i++) maps.desc[i] = (0x40000040ull << 32) + UD;
  maps.lut = lut;
  maps.pad = 0;
  constexpr Tab tab = make_tab();
  for (int t = 0; t < 66; t++) maps.tiles[t] = tab.tiles[t];
  for (int i = 0; i < 396; i++) maps.jobs[i] = tab.jobs[i];
  fused_kernel<<<NUM_CTAS, NTHREADS, SMEM_BYTES, cudaStreamPerThread>>>(count, lut, gp, qw, (const uint8_t*)x, maps.desc[0] - 2, maps);
}
```

```cpp
#include <cuda_runtime.h>
#include <cuda_bf16.h>
#include <cuda.h>
#include <stdint.h>
#include <cstdio>
#include <algorithm>

namespace {

constexpr int M_ = 2048, K_ = 1024, N_ = 3584;
constexpr int BF = 128, BK = 64;
constexpr int TA = 256, TB = 192;
#define TCC 232
constexpr int TC = TCC, TD = 184;
constexpr int STAGES = 4;
constexpr int KBLKS = K_ / BK;
constexpr int X_BYTES = TA * BK * 2;
constexpr int UNIT_BYTES = BK * 32 * 4;
constexpr int SLAB_BYTES = BF * BK;
constexpr int STAGE_BYTES = X_BYTES + SLAB_BYTES;
constexpr int OFF_STG = STAGES * STAGE_BYTES;
constexpr int OFF_PL = OFF_STG + 3 * UNIT_BYTES;
constexpr int OFF_TAB = OFF_PL + 2048;
constexpr int OFF_BAR = OFF_STG + 65536;
constexpr int W_OFF = 16 * KBLKS * SLAB_BYTES;
constexpr int SMEM_BYTES = OFF_BAR + 512;
constexpr int NUM_CTAS = 132;
constexpr int NTHREADS = 384;
constexpr int NPACK = 3;
#define XT0 2600
#define WT0 2350
#define WTS 1000
#define S1D 400
#define PC 900
#define OB 32
#define WD 0x2212
#define RB 1
#define D0 900
#define LT0 7800
#define LTS 16
#define XPROM CU_TENSOR_MAP_L2_PROMOTION_L2_128B
#define QPROM CU_TENSOR_MAP_L2_PROMOTION_L2_128B
#define NP 3
#define PN 16
#define W17 1
#define SB0 0
#define NSB 8
#define FEN 1
#define GMAP 1
#define EPW 1
#define LCAP 14000
#define NB3 1
#define ORD 1
#define PU 44
#define U0(r, p) (ORD == 3 ? 132 * (p) + 131 - (r) : ORD == 0 ? 3 * (r) + (p) : ORD == 1 ? 132 * (p) + (r) : (p) ? 131 + 2 * (r) + (p) : (r))
#define G0 WT0
#define G1 (WT0 + WTS)
#define G2 (WT0 + 2 * WTS)
#define G3 (WT0 + 3 * WTS)
#define G4 (WT0 + 4 * WTS - 150)
#define G5 (WT0 + 5 * WTS - 350)
#define G6 0
#define G7 0
#define G8 0
constexpr uint64_t GATES = (uint64_t)(G2 / 48) | (uint64_t)(G3 / 48) << 8 | (uint64_t)(G4 / 48) << 16 | (uint64_t)(G5 / 48) << 24 | (uint64_t)(G6 / 48) << 32 |
                           (uint64_t)(G7 / 48) << 40 | (uint64_t)(G8 / 48) << 48;
#define TR1 1
#define TR2 1
#define SW 0
#define XPD 2
#define XPS 2
#define XPW 1
#define SHF 1
#define PLF 1
#define EXF 1
#define PF 8
#define LD0 0
#define LPS 2
#define QD1 5
#define QN1 12
#define K0 4
#define QD0 3
#define QN0 8
#define FM0 0x100
#define K00 4
#define TCH 0
#define IX 8
#define UH 2
#define NA 13
#define UA 16
#define BF1 1
#define NTB 12
#define GB 7
#define W128 1
#define WP 0
#define RM 0x12
#define SMK 0xbaa9877654432110ull
#define SJ 0
#define DUP 1
#define T3 1
#define QD3 7
#define QN3 15
#define K3 6
#define HI 10
#define R24 0
#define UH3 1
#define K4 8
#define AD 2
#define BO 1
#define PEEL 0
#define TL 1
#define SLC 1
#define PADN 0
#define TOF 100
#define NX 2
#define WF 2
#define XPE 1
#define XP0 1600
#define XT2 0
#define XT3 0
#define THR 500
#define THS 50
#define W16 1
#define NBC 12
#define REV 0
#define UX 0
#define PB 28
#define PE 8500
#define PAR 0
#define SWP 1
#define U0A 16
#define PKI -2
#define EW 1
#define TCN 12
#define WI 7
#define NSH 2
static_assert(SMEM_BYTES <= 232448, "smem");
static_assert(TB * 128 + 2 * SLAB_BYTES == STAGE_BYTES, "stage");
static_assert(NX >= 2, "gates");
constexpr int B_FULL = 0, B_EMPTY = 4, B_DIR = 8, B_SLOT = 9, NBARS = 12, B_LAST = 16, B_SK = 32, B_RDY = B_DIR, B_W = 17, B_X = 18;
constexpr int OFF_EPOCH = OFF_BAR + 8 * NBARS;
constexpr uint32_t SB = 1024;
constexpr uint32_t UD = (SB >> 4) | (1u << 16);
enum { M_Q, M_D, M_XA, M_XC, M_XB, M_XD, M_O24, M_O32, M_O48, M_W, M_Q2, M_W2, NMAPS };

__device__ __align__(1024) uint8_t g_p[W_OFF + 12 * KBLKS * 2 * SLAB_BYTES];
__device__ __align__(128) unsigned int g_count[32 * 97];

__device__ __forceinline__ uint32_t smem_u32(const void* p) { return (uint32_t)__cvta_generic_to_shared(p); }
__device__ __forceinline__ void mbar_init(uint32_t bar, uint32_t cnt) {
  asm volatile("mbarrier.init.shared::cta.b64 [%0], %1;" ::"r"(bar), "r"(cnt) : "memory");
}
__device__ __forceinline__ void mbar_wait(uint32_t bar, uint32_t parity, uint32_t& c) {
  asm volatile(
      "{\n.reg .pred p;\n"
      "SPIN:\n"
      "mbarrier.try_wait.parity.shared::cta.b64 p, [%1], %2;\n"
      "add.u32 %0, %0, 1;\n"
      "setp.ge.or.u32 p, %0, 0x100000, p;\n"
      "@!p bra.uni SPIN;\n}\n"
      : "+r"(c) : "r"(bar), "r"(parity) : "memory");
}
__device__ __forceinline__ void mbar_wait_fast(uint32_t bar, uint32_t parity, uint32_t& c) {
  asm volatile(
      "{\n.reg .pred p;\n"
      "SPIN:\n"
      "mbarrier.try_wait.parity.shared::cta.b64 p, [%1], %2;\n"
      "@p bra.uni DONE;\n"
      "add.u32 %0, %0, 1;\n"
      "setp.lt.u32 p, %0, 0x100000;\n"
      "@p bra.uni SPIN;\n"
      "DONE:\n}\n"
      : "+r"(c) : "r"(bar), "r"(parity) : "memory");
}
__device__ __forceinline__ bool mbar_test(uint32_t bar, uint32_t parity) {
  uint32_t ok;
  asm volatile("{\n.reg .pred p;\nmbarrier.try_wait.parity.shared::cta.b64 p, [%1], %2;\nselp.u32 %0, 1, 0, p;\n}\n" : "=r"(ok) : "r"(bar), "r"(parity) : "memory");
  return ok != 0;
}
__device__ __forceinline__ bool mbar_peek(uint32_t bar, uint32_t parity) {
  uint32_t ok;
  asm volatile("{\n.reg .pred p;\nmbarrier.test_wait.parity.shared::cta.b64 p, [%1], %2;\nselp.u32 %0, 1, 0, p;\n}\n" : "=r"(ok) : "r"(bar), "r"(parity) : "memory");
  return ok != 0;
}
__device__ __forceinline__ void mbar_arrive(uint32_t bar) {
  asm volatile("mbarrier.arrive.shared::cta.b64 _, [%0];" ::"r"(bar) : "memory");
}
__device__ __forceinline__ uint32_t mapa(uint32_t a, uint32_t cta) {
  uint32_t r;
  asm("mapa.shared::cluster.u32 %0, %1, %2;" : "=r"(r) : "r"(a), "r"(cta));
  return r;
}
__device__ __forceinline__ void mbar_arrive_remote_if(uint32_t ra, uint32_t cond) {
  asm volatile("{\n.reg .pred p;\nsetp.ne.u32 p, %1, 0;\n@p mbarrier.arrive.shared::cluster.b64 _, [%0];\n}\n" ::"r"(ra), "r"(cond) : "memory");
}
#define ELECT "{\n.reg .pred p;\nelect.sync _|p, 0xffffffff;\n"
__device__ __forceinline__ void expect_w(uint32_t bar, uint32_t bytes) {
  asm volatile(ELECT "@p mbarrier.arrive.expect_tx.shared::cta.b64 _, [%0], %1;\n}\n" ::"r"(bar), "r"(bytes) : "memory");
}
__device__ __forceinline__ void arrive_w(uint32_t bar) {
  asm volatile(ELECT "@p mbarrier.arrive.shared::cta.b64 _, [%0];\n}\n" ::"r"(bar) : "memory");
}
__device__ __forceinline__ void tma_mc_w(uint32_t dst, const CUtensorMap* map, uint32_t bar, int c0, int c1) {
  asm volatile(
      ELECT "@p cp.async.bulk.tensor.2d.shared::cluster.global.mbarrier::complete_tx::bytes.multicast::cluster [%0], [%1, {%3, %4}], [%2], %5;\n}\n"
      ::"r"(dst), "l"((uint64_t)map), "r"(bar), "r"(c0), "r"(c1), "h"((uint16_t)3) : "memory");
}
__device__ __forceinline__ void wait_tma_mc_w(uint32_t wb, uint32_t parity, uint32_t& c, uint32_t dst, const CUtensorMap* map, uint32_t bar, int c0, int c1) {
  asm volatile(
      "{\n.reg .pred p;\n"
      "SPIN:\n"
      "mbarrier.try_wait.parity.shared::cta.b64 p, [%1], %2;\n"
      "add.u32 %0, %0, 1;\n"
      "setp.ge.or.u32 p, %0, 0x100000, p;\n"
      "@!p bra.uni SPIN;\n"
      "elect.sync _|p, 0xffffffff;\n"
      "@p cp.async.bulk.tensor.2d.shared::cluster.global.mbarrier::complete_tx::bytes.multicast::cluster [%3], [%4, {%6, %7}], [%5], %8;\n}\n"
      : "+r"(c) : "r"(wb), "r"(parity), "r"(dst), "l"((uint64_t)map), "r"(bar), "r"(c0), "r"(c1), "h"((uint16_t)3) : "memory");
}
__device__ __forceinline__ void bulk_w(uint32_t dst, const void* src, uint32_t bytes, uint32_t bar) {
  asm volatile(ELECT "@p cp.async.bulk.shared::cluster.global.mbarrier::complete_tx::bytes [%0], [%1], %2, [%3];\n}\n"
               ::"r"(dst), "l"(src), "r"(bytes), "r"(bar) : "memory");
}
__device__ __forceinline__ void tma_w(uint32_t dst, const CUtensorMap* map, uint32_t bar, int c0, int c1) {
  asm volatile(
      ELECT "@p cp.async.bulk.tensor.2d.shared::cluster.global.mbarrier::complete_tx::bytes [%0], [%1, {%3, %4}], [%2];\n}\n"
      ::"r"(dst), "l"((uint64_t)map), "r"(bar), "r"(c0), "r"(c1) : "memory");
}
__device__ __forceinline__ void tma3_w(uint32_t dst, const CUtensorMap* map, uint32_t bar, int c0, int c1, int c2) {
  asm volatile(
      ELECT "@p cp.async.bulk.tensor.3d.shared::cluster.global.mbarrier::complete_tx::bytes [%0], [%1, {%3, %4, %5}], [%2];\n}\n"
      ::"r"(dst), "l"((uint64_t)map), "r"(bar), "r"(c0), "r"(c1), "r"(c2) : "memory");
}
__device__ __forceinline__ void store_w(const CUtensorMap* map, uint32_t src, int c0, int c1) {
  asm volatile(ELECT "@p cp.async.bulk.tensor.2d.global.shared::cta.bulk_group [%0, {%2, %3}], [%1];\n}\n"
               "cp.async.bulk.commit_group;"
               ::"l"((uint64_t)map), "r"(src), "r"(c0), "r"(c1) : "memory");
}
__device__ __forceinline__ void bulk_wait_read() { asm volatile("cp.async.bulk.wait_group.read 0;" ::: "memory"); }
__device__ __forceinline__ void cluster_arrive_relaxed() { asm volatile("barrier.cluster.arrive.relaxed.aligned;" ::: "memory"); }
__device__ __forceinline__ void cluster_wait() { asm volatile("barrier.cluster.wait.acquire.aligned;" ::: "memory"); }
__device__ __forceinline__ void wgmma_fence() { asm volatile("wgmma.fence.sync.aligned;" ::: "memory"); }
__device__ __forceinline__ void wgmma_commit() { asm volatile("wgmma.commit_group.sync.aligned;" ::: "memory"); }
template <int N> __device__ __forceinline__ void wgmma_wait() { asm volatile("wgmma.wait_group.sync.aligned %0;" ::"n"(N) : "memory"); }
template <int N> __device__ __forceinline__ void fence_regs(float (&p)[N]) {
#pragma unroll
  for (int i = 0; i < N; i++) asm volatile("" : "+f"(p[i]) :: "memory");
}

template <int N> __device__ __forceinline__ void wgmma_rs(float* d, const uint32_t* a, uint32_t descB, uint32_t accum);
template <> __device__ __forceinline__ void wgmma_rs<40>(float* d, const uint32_t* a, uint32_t descB, uint32_t accum) {
  asm volatile(
    "{\n.reg .pred p;\n.reg .b64 db;\n"
    "setp.ne.b32 p, %25, 0;\n"
    "mov.b64 db, {%24, 0x40000040};\n"
    "wgmma.mma_async.sync.aligned.m64n40k16.f32.bf16.bf16 "
    "{%0, %1, %2, %3, %4, %5, %6, %7, %8, %9, %10, %11, %12, %13, %14, %15, %16, %17, %18, %19}, "
    "{%20, %21, %22, %23}, db, p, 1, 1, 0;\n"
    "}\n"
    : "+f"(d[0]), "+f"(d[1]), "+f"(d[2]), "+f"(d[3]), "+f"(d[4]), "+f"(d[5]), "+f"(d[6]), "+f"(d[7]), "+f"(d[8]), "+f"(d[9]), "+f"(d[10]), "+f"(d[11]), "+f"(d[12]), "+f"(d[13]), "+f"(d[14]), "+f"(d[15]), "+f"(d[16]), "+f"(d[17]), "+f"(d[18]), "+f"(d[19])
    : "r"(a[0]), "r"(a[1]), "r"(a[2]), "r"(a[3]), "r"(descB), "r"(accum));
}
template <> __device__ __forceinline__ void wgmma_rs<32>(float* d, const uint32_t* a, uint32_t descB, uint32_t accum) {
  asm volatile(
    "{\n.reg .pred p;\n.reg .b64 db;\n"
    "setp.ne.b32 p, %21, 0;\n"
    "mov.b64 db, {%20, 0x40000040};\n"
    "wgmma.mma_async.sync.aligned.m64n32k16.f32.bf16.bf16 "
    "{%0, %1, %2, %3, %4, %5, %6, %7, %8, %9, %10, %11, %12, %13, %14, %15}, "
    "{%16, %17, %18, %19}, db, p, 1, 1, 0;\n"
    "}\n"
    : "+f"(d[0]), "+f"(d[1]), "+f"(d[2]), "+f"(d[3]), "+f"(d[4]), "+f"(d[5]), "+f"(d[6]), "+f"(d[7]), "+f"(d[8]), "+f"(d[9]), "+f"(d[10]), "+f"(d[11]), "+f"(d[12]), "+f"(d[13]), "+f"(d[14]), "+f"(d[15])
    : "r"(a[0]), "r"(a[1]), "r"(a[2]), "r"(a[3]), "r"(descB), "r"(accum));
}
template <> __device__ __forceinline__ void wgmma_rs<24>(float* d, const uint32_t* a, uint32_t descB, uint32_t accum) {
  asm volatile(
    "{\n.reg .pred p;\n.reg .b64 db;\n"
    "setp.ne.b32 p, %17, 0;\n"
    "mov.b64 db, {%16, 0x40000040};\n"
    "wgmma.mma_async.sync.aligned.m64n24k16.f32.bf16.bf16 "
    "{%0, %1, %2, %3, %4, %5, %6, %7, %8, %9, %10, %11}, "
    "{%12, %13, %14, %15}, db, p, 1, 1, 0;\n"
    "}\n"
    : "+f"(d[0]), "+f"(d[1]), "+f"(d[2]), "+f"(d[3]), "+f"(d[4]), "+f"(d[5]), "+f"(d[6]), "+f"(d[7]), "+f"(d[8]), "+f"(d[9]), "+f"(d[10]), "+f"(d[11])
    : "r"(a[0]), "r"(a[1]), "r"(a[2]), "r"(a[3]), "r"(descB), "r"(accum));
}

template <int N> __device__ __forceinline__ void wgmma_rp(float* d, const uint32_t* a, uint64_t descB, uint32_t accum);
template <> __device__ __forceinline__ void wgmma_rp<256>(float* d, const uint32_t* a, uint64_t descB, uint32_t accum) {
  asm volatile(
    "{\n.reg .pred p;\n.reg .b64 db;\n"
    "setp.ne.b32 p, %133, 0;\n"
    "mov.b64 db, %132;\n"
    "wgmma.mma_async.sync.aligned.m64n256k16.f32.bf16.bf16 "
    "{%0, %1, %2, %3, %4, %5, %6, %7, %8, %9, %10, %11, %12, %13, %14, %15, %16, %17, %18, %19, %20, %21, %22, %23, %24, %25, %26, %27, %28, %29, %30, %31, %32, %33, %34, %35, %36, %37, %38, %39, %40, %41, %42, %43, %44, %45, %46, %47, %48, %49, %50, %51, %52, %53, %54, %55, %56, %57, %58, %59, %60, %61, %62, %63, %64, %65, %66, %67, %68, %69, %70, %71, %72, %73, %74, %75, %76, %77, %78, %79, %80, %81, %82, %83, %84, %85, %86, %87, %88, %89, %90, %91, %92, %93, %94, %95, %96, %97, %98, %99, %100, %101, %102, %103, %104, %105, %106, %107, %108, %109, %110, %111, %112, %113, %114, %115, %116, %117, %118, %119, %120, %121, %122, %123, %124, %125, %126, %127}, "
    "{%128, %129, %130, %131}, db, p, 1, 1, 0;\n"
    "}\n"
    : "+f"(d[0]), "+f"(d[1]), "+f"(d[2]), "+f"(d[3]), "+f"(d[4]), "+f"(d[5]), "+f"(d[6]), "+f"(d[7]), "+f"(d[8]), "+f"(d[9]), "+f"(d[10]), "+f"(d[11]), "+f"(d[12]), "+f"(d[13]), "+f"(d[14]), "+f"(d[15]), "+f"(d[16]), "+f"(d[17]), "+f"(d[18]), "+f"(d[19]), "+f"(d[20]), "+f"(d[21]), "+f"(d[22]), "+f"(d[23]), "+f"(d[24]), "+f"(d[25]), "+f"(d[26]), "+f"(d[27]), "+f"(d[28]), "+f"(d[29]), "+f"(d[30]), "+f"(d[31]), "+f"(d[32]), "+f"(d[33]), "+f"(d[34]), "+f"(d[35]), "+f"(d[36]), "+f"(d[37]), "+f"(d[38]), "+f"(d[39]), "+f"(d[40]), "+f"(d[41]), "+f"(d[42]), "+f"(d[43]), "+f"(d[44]), "+f"(d[45]), "+f"(d[46]), "+f"(d[47]), "+f"(d[48]), "+f"(d[49]), "+f"(d[50]), "+f"(d[51]), "+f"(d[52]), "+f"(d[53]), "+f"(d[54]), "+f"(d[55]), "+f"(d[56]), "+f"(d[57]), "+f"(d[58]), "+f"(d[59]), "+f"(d[60]), "+f"(d[61]), "+f"(d[62]), "+f"(d[63]), "+f"(d[64]), "+f"(d[65]), "+f"(d[66]), "+f"(d[67]), "+f"(d[68]), "+f"(d[69]), "+f"(d[70]), "+f"(d[71]), "+f"(d[72]), "+f"(d[73]), "+f"(d[74]), "+f"(d[75]), "+f"(d[76]), "+f"(d[77]), "+f"(d[78]), "+f"(d[79]), "+f"(d[80]), "+f"(d[81]), "+f"(d[82]), "+f"(d[83]), "+f"(d[84]), "+f"(d[85]), "+f"(d[86]), "+f"(d[87]), "+f"(d[88]), "+f"(d[89]), "+f"(d[90]), "+f"(d[91]), "+f"(d[92]), "+f"(d[93]), "+f"(d[94]), "+f"(d[95]), "+f"(d[96]), "+f"(d[97]), "+f"(d[98]), "+f"(d[99]), "+f"(d[100]), "+f"(d[101]), "+f"(d[102]), "+f"(d[103]), "+f"(d[104]), "+f"(d[105]), "+f"(d[106]), "+f"(d[107]), "+f"(d[108]), "+f"(d[109]), "+f"(d[110]), "+f"(d[111]), "+f"(d[112]), "+f"(d[113]), "+f"(d[114]), "+f"(d[115]), "+f"(d[116]), "+f"(d[117]), "+f"(d[118]), "+f"(d[119]), "+f"(d[120]), "+f"(d[121]), "+f"(d[122]), "+f"(d[123]), "+f"(d[124]), "+f"(d[125]), "+f"(d[126]), "+f"(d[127])
    : "r"(a[0]), "r"(a[1]), "r"(a[2]), "r"(a[3]), "l"(descB), "r"(accum));
}
template <> __device__ __forceinline__ void wgmma_rp<232>(float* d, const uint32_t* a, uint64_t descB, uint32_t accum) {
  asm volatile(
    "{\n.reg .pred p;\n.reg .b64 db;\n"
    "setp.ne.b32 p, %121, 0;\n"
    "mov.b64 db, %120;\n"
    "wgmma.mma_async.sync.aligned.m64n232k16.f32.bf16.bf16 "
    "{%0, %1, %2, %3, %4, %5, %6, %7, %8, %9, %10, %11, %12, %13, %14, %15, %16, %17, %18, %19, %20, %21, %22, %23, %24, %25, %26, %27, %28, %29, %30, %31, %32, %33, %34, %35, %36, %37, %38, %39, %40, %41, %42, %43, %44, %45, %46, %47, %48, %49, %50, %51, %52, %53, %54, %55, %56, %57, %58, %59, %60, %61, %62, %63, %64, %65, %66, %67, %68, %69, %70, %71, %72, %73, %74, %75, %76, %77, %78, %79, %80, %81, %82, %83, %84, %85, %86, %87, %88, %89, %90, %91, %92, %93, %94, %95, %96, %97, %98, %99, %100, %101, %102, %103, %104, %105, %106, %107, %108, %109, %110, %111, %112, %113, %114, %115}, "
    "{%116, %117, %118, %119}, db, p, 1, 1, 0;\n"
    "}\n"
    : "+f"(d[0]), "+f"(d[1]), "+f"(d[2]), "+f"(d[3]), "+f"(d[4]), "+f"(d[5]), "+f"(d[6]), "+f"(d[7]), "+f"(d[8]), "+f"(d[9]), "+f"(d[10]), "+f"(d[11]), "+f"(d[12]), "+f"(d[13]), "+f"(d[14]), "+f"(d[15]), "+f"(d[16]), "+f"(d[17]), "+f"(d[18]), "+f"(d[19]), "+f"(d[20]), "+f"(d[21]), "+f"(d[22]), "+f"(d[23]), "+f"(d[24]), "+f"(d[25]), "+f"(d[26]), "+f"(d[27]), "+f"(d[28]), "+f"(d[29]), "+f"(d[30]), "+f"(d[31]), "+f"(d[32]), "+f"(d[33]), "+f"(d[34]), "+f"(d[35]), "+f"(d[36]), "+f"(d[37]), "+f"(d[38]), "+f"(d[39]), "+f"(d[40]), "+f"(d[41]), "+f"(d[42]), "+f"(d[43]), "+f"(d[44]), "+f"(d[45]), "+f"(d[46]), "+f"(d[47]), "+f"(d[48]), "+f"(d[49]), "+f"(d[50]), "+f"(d[51]), "+f"(d[52]), "+f"(d[53]), "+f"(d[54]), "+f"(d[55]), "+f"(d[56]), "+f"(d[57]), "+f"(d[58]), "+f"(d[59]), "+f"(d[60]), "+f"(d[61]), "+f"(d[62]), "+f"(d[63]), "+f"(d[64]), "+f"(d[65]), "+f"(d[66]), "+f"(d[67]), "+f"(d[68]), "+f"(d[69]), "+f"(d[70]), "+f"(d[71]), "+f"(d[72]), "+f"(d[73]), "+f"(d[74]), "+f"(d[75]), "+f"(d[76]), "+f"(d[77]), "+f"(d[78]), "+f"(d[79]), "+f"(d[80]), "+f"(d[81]), "+f"(d[82]), "+f"(d[83]), "+f"(d[84]), "+f"(d[85]), "+f"(d[86]), "+f"(d[87]), "+f"(d[88]), "+f"(d[89]), "+f"(d[90]), "+f"(d[91]), "+f"(d[92]), "+f"(d[93]), "+f"(d[94]), "+f"(d[95]), "+f"(d[96]), "+f"(d[97]), "+f"(d[98]), "+f"(d[99]), "+f"(d[100]), "+f"(d[101]), "+f"(d[102]), "+f"(d[103]), "+f"(d[104]), "+f"(d[105]), "+f"(d[106]), "+f"(d[107]), "+f"(d[108]), "+f"(d[109]), "+f"(d[110]), "+f"(d[111]), "+f"(d[112]), "+f"(d[113]), "+f"(d[114]), "+f"(d[115])
    : "r"(a[0]), "r"(a[1]), "r"(a[2]), "r"(a[3]), "l"(descB), "r"(accum));
}

template <int N> __device__ __forceinline__ void wgmma_rl(float* d, const uint32_t* a, uint64_t descB);
template <> __device__ __forceinline__ void wgmma_rl<48>(float* d, const uint32_t* a, uint64_t descB) {
  asm volatile(
    "wgmma.mma_async.sync.aligned.m64n48k16.f32.bf16.bf16 "
    "{%0, %1, %2, %3, %4, %5, %6, %7, %8, %9, %10, %11, %12, %13, %14, %15, %16, %17, %18, %19, %20, %21, %22, %23}, "
    "{%24, %25, %26, %27}, %28, 1, 1, 1, 0;\n"
    : "+f"(d[0]), "+f"(d[1]), "+f"(d[2]), "+f"(d[3]), "+f"(d[4]), "+f"(d[5]), "+f"(d[6]), "+f"(d[7]), "+f"(d[8]), "+f"(d[9]), "+f"(d[10]), "+f"(d[11]), "+f"(d[12]), "+f"(d[13]), "+f"(d[14]), "+f"(d[15]), "+f"(d[16]), "+f"(d[17]), "+f"(d[18]), "+f"(d[19]), "+f"(d[20]), "+f"(d[21]), "+f"(d[22]), "+f"(d[23])
    : "r"(a[0]), "r"(a[1]), "r"(a[2]), "r"(a[3]), "l"(descB));
}
template <> __device__ __forceinline__ void wgmma_rl<32>(float* d, const uint32_t* a, uint64_t descB) {
  asm volatile(
    "wgmma.mma_async.sync.aligned.m64n32k16.f32.bf16.bf16 "
    "{%0, %1, %2, %3, %4, %5, %6, %7, %8, %9, %10, %11, %12, %13, %14, %15}, "
    "{%16, %17, %18, %19}, %20, 1, 1, 1, 0;\n"
    : "+f"(d[0]), "+f"(d[1]), "+f"(d[2]), "+f"(d[3]), "+f"(d[4]), "+f"(d[5]), "+f"(d[6]), "+f"(d[7]), "+f"(d[8]), "+f"(d[9]), "+f"(d[10]), "+f"(d[11]), "+f"(d[12]), "+f"(d[13]), "+f"(d[14]), "+f"(d[15])
    : "r"(a[0]), "r"(a[1]), "r"(a[2]), "r"(a[3]), "l"(descB));
}
template <> __device__ __forceinline__ void wgmma_rl<24>(float* d, const uint32_t* a, uint64_t descB) {
  asm volatile(
    "wgmma.mma_async.sync.aligned.m64n24k16.f32.bf16.bf16 "
    "{%0, %1, %2, %3, %4, %5, %6, %7, %8, %9, %10, %11}, "
    "{%12, %13, %14, %15}, %16, 1, 1, 1, 0;\n"
    : "+f"(d[0]), "+f"(d[1]), "+f"(d[2]), "+f"(d[3]), "+f"(d[4]), "+f"(d[5]), "+f"(d[6]), "+f"(d[7]), "+f"(d[8]), "+f"(d[9]), "+f"(d[10]), "+f"(d[11])
    : "r"(a[0]), "r"(a[1]), "r"(a[2]), "r"(a[3]), "l"(descB));
}
template <> __device__ __forceinline__ void wgmma_rl<232>(float* d, const uint32_t* a, uint64_t descB) {
  asm volatile(
    "wgmma.mma_async.sync.aligned.m64n232k16.f32.bf16.bf16 "
    "{%0, %1, %2, %3, %4, %5, %6, %7, %8, %9, %10, %11, %12, %13, %14, %15, %16, %17, %18, %19, %20, %21, %22, %23, %24, %25, %26, %27, %28, %29, %30, %31, %32, %33, %34, %35, %36, %37, %38, %39, %40, %41, %42, %43, %44, %45, %46, %47, %48, %49, %50, %51, %52, %53, %54, %55, %56, %57, %58, %59, %60, %61, %62, %63, %64, %65, %66, %67, %68, %69, %70, %71, %72, %73, %74, %75, %76, %77, %78, %79, %80, %81, %82, %83, %84, %85, %86, %87, %88, %89, %90, %91, %92, %93, %94, %95, %96, %97, %98, %99, %100, %101, %102, %103, %104, %105, %106, %107, %108, %109, %110, %111, %112, %113, %114, %115}, "
    "{%116, %117, %118, %119}, %120, 1, 1, 1, 0;\n"
    : "+f"(d[0]), "+f"(d[1]), "+f"(d[2]), "+f"(d[3]), "+f"(d[4]), "+f"(d[5]), "+f"(d[6]), "+f"(d[7]), "+f"(d[8]), "+f"(d[9]), "+f"(d[10]), "+f"(d[11]), "+f"(d[12]), "+f"(d[13]), "+f"(d[14]), "+f"(d[15]), "+f"(d[16]), "+f"(d[17]), "+f"(d[18]), "+f"(d[19]), "+f"(d[20]), "+f"(d[21]), "+f"(d[22]), "+f"(d[23]), "+f"(d[24]), "+f"(d[25]), "+f"(d[26]), "+f"(d[27]), "+f"(d[28]), "+f"(d[29]), "+f"(d[30]), "+f"(d[31]), "+f"(d[32]), "+f"(d[33]), "+f"(d[34]), "+f"(d[35]), "+f"(d[36]), "+f"(d[37]), "+f"(d[38]), "+f"(d[39]), "+f"(d[40]), "+f"(d[41]), "+f"(d[42]), "+f"(d[43]), "+f"(d[44]), "+f"(d[45]), "+f"(d[46]), "+f"(d[47]), "+f"(d[48]), "+f"(d[49]), "+f"(d[50]), "+f"(d[51]), "+f"(d[52]), "+f"(d[53]), "+f"(d[54]), "+f"(d[55]), "+f"(d[56]), "+f"(d[57]), "+f"(d[58]), "+f"(d[59]), "+f"(d[60]), "+f"(d[61]), "+f"(d[62]), "+f"(d[63]), "+f"(d[64]), "+f"(d[65]), "+f"(d[66]), "+f"(d[67]), "+f"(d[68]), "+f"(d[69]), "+f"(d[70]), "+f"(d[71]), "+f"(d[72]), "+f"(d[73]), "+f"(d[74]), "+f"(d[75]), "+f"(d[76]), "+f"(d[77]), "+f"(d[78]), "+f"(d[79]), "+f"(d[80]), "+f"(d[81]), "+f"(d[82]), "+f"(d[83]), "+f"(d[84]), "+f"(d[85]), "+f"(d[86]), "+f"(d[87]), "+f"(d[88]), "+f"(d[89]), "+f"(d[90]), "+f"(d[91]), "+f"(d[92]), "+f"(d[93]), "+f"(d[94]), "+f"(d[95]), "+f"(d[96]), "+f"(d[97]), "+f"(d[98]), "+f"(d[99]), "+f"(d[100]), "+f"(d[101]), "+f"(d[102]), "+f"(d[103]), "+f"(d[104]), "+f"(d[105]), "+f"(d[106]), "+f"(d[107]), "+f"(d[108]), "+f"(d[109]), "+f"(d[110]), "+f"(d[111]), "+f"(d[112]), "+f"(d[113]), "+f"(d[114]), "+f"(d[115])
    : "r"(a[0]), "r"(a[1]), "r"(a[2]), "r"(a[3]), "l"(descB));
}
template <> __device__ __forceinline__ void wgmma_rl<256>(float* d, const uint32_t* a, uint64_t descB) {
  asm volatile(
    "wgmma.mma_async.sync.aligned.m64n256k16.f32.bf16.bf16 "
    "{%0, %1, %2, %3, %4, %5, %6, %7, %8, %9, %10, %11, %12, %13, %14, %15, %16, %17, %18, %19, %20, %21, %22, %23, %24, %25, %26, %27, %28, %29, %30, %31, %32, %33, %34, %35, %36, %37, %38, %39, %40, %41, %42, %43, %44, %45, %46, %47, %48, %49, %50, %51, %52, %53, %54, %55, %56, %57, %58, %59, %60, %61, %62, %63, %64, %65, %66, %67, %68, %69, %70, %71, %72, %73, %74, %75, %76, %77, %78, %79, %80, %81, %82, %83, %84, %85, %86, %87, %88, %89, %90, %91, %92, %93, %94, %95, %96, %97, %98, %99, %100, %101, %102, %103, %104, %105, %106, %107, %108, %109, %110, %111, %112, %113, %114, %115, %116, %117, %118, %119, %120, %121, %122, %123, %124, %125, %126, %127}, "
    "{%128, %129, %130, %131}, %132, 1, 1, 1, 0;\n"
    : "+f"(d[0]), "+f"(d[1]), "+f"(d[2]), "+f"(d[3]), "+f"(d[4]), "+f"(d[5]), "+f"(d[6]), "+f"(d[7]), "+f"(d[8]), "+f"(d[9]), "+f"(d[10]), "+f"(d[11]), "+f"(d[12]), "+f"(d[13]), "+f"(d[14]), "+f"(d[15]), "+f"(d[16]), "+f"(d[17]), "+f"(d[18]), "+f"(d[19]), "+f"(d[20]), "+f"(d[21]), "+f"(d[22]), "+f"(d[23]), "+f"(d[24]), "+f"(d[25]), "+f"(d[26]), "+f"(d[27]), "+f"(d[28]), "+f"(d[29]), "+f"(d[30]), "+f"(d[31]), "+f"(d[32]), "+f"(d[33]), "+f"(d[34]), "+f"(d[35]), "+f"(d[36]), "+f"(d[37]), "+f"(d[38]), "+f"(d[39]), "+f"(d[40]), "+f"(d[41]), "+f"(d[42]), "+f"(d[43]), "+f"(d[44]), "+f"(d[45]), "+f"(d[46]), "+f"(d[47]), "+f"(d[48]), "+f"(d[49]), "+f"(d[50]), "+f"(d[51]), "+f"(d[52]), "+f"(d[53]), "+f"(d[54]), "+f"(d[55]), "+f"(d[56]), "+f"(d[57]), "+f"(d[58]), "+f"(d[59]), "+f"(d[60]), "+f"(d[61]), "+f"(d[62]), "+f"(d[63]), "+f"(d[64]), "+f"(d[65]), "+f"(d[66]), "+f"(d[67]), "+f"(d[68]), "+f"(d[69]), "+f"(d[70]), "+f"(d[71]), "+f"(d[72]), "+f"(d[73]), "+f"(d[74]), "+f"(d[75]), "+f"(d[76]), "+f"(d[77]), "+f"(d[78]), "+f"(d[79]), "+f"(d[80]), "+f"(d[81]), "+f"(d[82]), "+f"(d[83]), "+f"(d[84]), "+f"(d[85]), "+f"(d[86]), "+f"(d[87]), "+f"(d[88]), "+f"(d[89]), "+f"(d[90]), "+f"(d[91]), "+f"(d[92]), "+f"(d[93]), "+f"(d[94]), "+f"(d[95]), "+f"(d[96]), "+f"(d[97]), "+f"(d[98]), "+f"(d[99]), "+f"(d[100]), "+f"(d[101]), "+f"(d[102]), "+f"(d[103]), "+f"(d[104]), "+f"(d[105]), "+f"(d[106]), "+f"(d[107]), "+f"(d[108]), "+f"(d[109]), "+f"(d[110]), "+f"(d[111]), "+f"(d[112]), "+f"(d[113]), "+f"(d[114]), "+f"(d[115]), "+f"(d[116]), "+f"(d[117]), "+f"(d[118]), "+f"(d[119]), "+f"(d[120]), "+f"(d[121]), "+f"(d[122]), "+f"(d[123]), "+f"(d[124]), "+f"(d[125]), "+f"(d[126]), "+f"(d[127])
    : "r"(a[0]), "r"(a[1]), "r"(a[2]), "r"(a[3]), "l"(descB));
}

template <int N> __device__ __forceinline__ void wgmma_ss(float* d, uint64_t descA, uint64_t descB, uint32_t accum);
template <> __device__ __forceinline__ void wgmma_ss<192>(float* d, uint64_t descA, uint64_t descB, uint32_t accum) {
  asm volatile(
    "{\n.reg .pred p;\n"
    "setp.ne.b32 p, %98, 0;\n"
    "wgmma.mma_async.sync.aligned.m64n192k16.f32.bf16.bf16 "
    "{%0, %1, %2, %3, %4, %5, %6, %7, %8, %9, %10, %11, %12, %13, %14, %15, %16, %17, %18, %19, %20, %21, %22, %23, %24, %25, %26, %27, %28, %29, %30, %31, %32, %33, %34, %35, %36, %37, %38, %39, %40, %41, %42, %43, %44, %45, %46, %47, %48, %49, %50, %51, %52, %53, %54, %55, %56, %57, %58, %59, %60, %61, %62, %63, %64, %65, %66, %67, %68, %69, %70, %71, %72, %73, %74, %75, %76, %77, %78, %79, %80, %81, %82, %83, %84, %85, %86, %87, %88, %89, %90, %91, %92, %93, %94, %95}, "
    "%96, %97, p, 1, 1, 0, 0;\n"
    "}\n"
    : "+f"(d[0]), "+f"(d[1]), "+f"(d[2]), "+f"(d[3]), "+f"(d[4]), "+f"(d[5]), "+f"(d[6]), "+f"(d[7]), "+f"(d[8]), "+f"(d[9]), "+f"(d[10]), "+f"(d[11]), "+f"(d[12]), "+f"(d[13]), "+f"(d[14]), "+f"(d[15]), "+f"(d[16]), "+f"(d[17]), "+f"(d[18]), "+f"(d[19]), "+f"(d[20]), "+f"(d[21]), "+f"(d[22]), "+f"(d[23]), "+f"(d[24]), "+f"(d[25]), "+f"(d[26]), "+f"(d[27]), "+f"(d[28]), "+f"(d[29]), "+f"(d[30]), "+f"(d[31]), "+f"(d[32]), "+f"(d[33]), "+f"(d[34]), "+f"(d[35]), "+f"(d[36]), "+f"(d[37]), "+f"(d[38]), "+f"(d[39]), "+f"(d[40]), "+f"(d[41]), "+f"(d[42]), "+f"(d[43]), "+f"(d[44]), "+f"(d[45]), "+f"(d[46]), "+f"(d[47]), "+f"(d[48]), "+f"(d[49]), "+f"(d[50]), "+f"(d[51]), "+f"(d[52]), "+f"(d[53]), "+f"(d[54]), "+f"(d[55]), "+f"(d[56]), "+f"(d[57]), "+f"(d[58]), "+f"(d[59]), "+f"(d[60]), "+f"(d[61]), "+f"(d[62]), "+f"(d[63]), "+f"(d[64]), "+f"(d[65]), "+f"(d[66]), "+f"(d[67]), "+f"(d[68]), "+f"(d[69]), "+f"(d[70]), "+f"(d[71]), "+f"(d[72]), "+f"(d[73]), "+f"(d[74]), "+f"(d[75]), "+f"(d[76]), "+f"(d[77]), "+f"(d[78]), "+f"(d[79]), "+f"(d[80]), "+f"(d[81]), "+f"(d[82]), "+f"(d[83]), "+f"(d[84]), "+f"(d[85]), "+f"(d[86]), "+f"(d[87]), "+f"(d[88]), "+f"(d[89]), "+f"(d[90]), "+f"(d[91]), "+f"(d[92]), "+f"(d[93]), "+f"(d[94]), "+f"(d[95])
    : "l"(descA), "l"(descB), "r"(accum));
}
template <> __device__ __forceinline__ void wgmma_ss<184>(float* d, uint64_t descA, uint64_t descB, uint32_t accum) {
  asm volatile(
    "{\n.reg .pred p;\n"
    "setp.ne.b32 p, %94, 0;\n"
    "wgmma.mma_async.sync.aligned.m64n184k16.f32.bf16.bf16 "
    "{%0, %1, %2, %3, %4, %5, %6, %7, %8, %9, %10, %11, %12, %13, %14, %15, %16, %17, %18, %19, %20, %21, %22, %23, %24, %25, %26, %27, %28, %29, %30, %31, %32, %33, %34, %35, %36, %37, %38, %39, %40, %41, %42, %43, %44, %45, %46, %47, %48, %49, %50, %51, %52, %53, %54, %55, %56, %57, %58, %59, %60, %61, %62, %63, %64, %65, %66, %67, %68, %69, %70, %71, %72, %73, %74, %75, %76, %77, %78, %79, %80, %81, %82, %83, %84, %85, %86, %87, %88, %89, %90, %91}, "
    "%92, %93, p, 1, 1, 0, 0;\n"
    "}\n"
    : "+f"(d[0]), "+f"(d[1]), "+f"(d[2]), "+f"(d[3]), "+f"(d[4]), "+f"(d[5]), "+f"(d[6]), "+f"(d[7]), "+f"(d[8]), "+f"(d[9]), "+f"(d[10]), "+f"(d[11]), "+f"(d[12]), "+f"(d[13]), "+f"(d[14]), "+f"(d[15]), "+f"(d[16]), "+f"(d[17]), "+f"(d[18]), "+f"(d[19]), "+f"(d[20]), "+f"(d[21]), "+f"(d[22]), "+f"(d[23]), "+f"(d[24]), "+f"(d[25]), "+f"(d[26]), "+f"(d[27]), "+f"(d[28]), "+f"(d[29]), "+f"(d[30]), "+f"(d[31]), "+f"(d[32]), "+f"(d[33]), "+f"(d[34]), "+f"(d[35]), "+f"(d[36]), "+f"(d[37]), "+f"(d[38]), "+f"(d[39]), "+f"(d[40]), "+f"(d[41]), "+f"(d[42]), "+f"(d[43]), "+f"(d[44]), "+f"(d[45]), "+f"(d[46]), "+f"(d[47]), "+f"(d[48]), "+f"(d[49]), "+f"(d[50]), "+f"(d[51]), "+f"(d[52]), "+f"(d[53]), "+f"(d[54]), "+f"(d[55]), "+f"(d[56]), "+f"(d[57]), "+f"(d[58]), "+f"(d[59]), "+f"(d[60]), "+f"(d[61]), "+f"(d[62]), "+f"(d[63]), "+f"(d[64]), "+f"(d[65]), "+f"(d[66]), "+f"(d[67]), "+f"(d[68]), "+f"(d[69]), "+f"(d[70]), "+f"(d[71]), "+f"(d[72]), "+f"(d[73]), "+f"(d[74]), "+f"(d[75]), "+f"(d[76]), "+f"(d[77]), "+f"(d[78]), "+f"(d[79]), "+f"(d[80]), "+f"(d[81]), "+f"(d[82]), "+f"(d[83]), "+f"(d[84]), "+f"(d[85]), "+f"(d[86]), "+f"(d[87]), "+f"(d[88]), "+f"(d[89]), "+f"(d[90]), "+f"(d[91])
    : "l"(descA), "l"(descB), "r"(accum));
}

template <int N> struct IC { static constexpr int v = N; };

__device__ __forceinline__ void stmatrix_x4_t(uint32_t addr, uint32_t r0, uint32_t r1, uint32_t r2, uint32_t r3) {
  asm volatile("stmatrix.sync.aligned.m8n8.x4.trans.shared.b16 [%0], {%1, %2, %3, %4};"
               ::"r"(addr), "r"(r0), "r"(r1), "r"(r2), "r"(r3) : "memory");
}
__device__ __forceinline__ void ldmatrix_x4(uint32_t* r, uint32_t addr) {
  asm volatile("ldmatrix.sync.aligned.m8n8.x4.shared.b16 {%0, %1, %2, %3}, [%4];"
               : "=r"(r[0]), "=r"(r[1]), "=r"(r[2]), "=r"(r[3]) : "r"(addr) : "memory");
}
__device__ __forceinline__ void ldmatrix_x4_if(uint32_t* r, uint32_t addr, uint32_t c) {
  asm volatile("{\n.reg .pred p;\nsetp.eq.u32 p, %5, 0;\n@p ldmatrix.sync.aligned.m8n8.x4.shared.b16 {%0, %1, %2, %3}, [%4];\n}\n"
               : "+r"(r[0]), "+r"(r[1]), "+r"(r[2]), "+r"(r[3]) : "r"(addr), "r"(c) : "memory");
}
__device__ __forceinline__ uint32_t pack_bf16(float a, float b) {
  __nv_bfloat162 v = __floats2bfloat162_rn(a, b);
  return *reinterpret_cast<uint32_t*>(&v);
}
__device__ __forceinline__ uint32_t prmt(uint32_t a, uint32_t b, uint32_t s) {
  uint32_t d;
  asm("prmt.b32 %0, %1, %2, %3;" : "=r"(d) : "r"(a), "r"(b), "r"(s));
  return d;
}
__device__ __forceinline__ uint32_t lds32(uint32_t a) {
  uint32_t v;
  asm volatile("ld.shared.u32 %0, [%1];" : "=r"(v) : "r"(a) : "memory");
  return v;
}
__device__ __forceinline__ void lds128(uint32_t* v, uint32_t a) {
  asm volatile("ld.shared.v4.u32 {%0, %1, %2, %3}, [%4];" : "=r"(v[0]), "=r"(v[1]), "=r"(v[2]), "=r"(v[3]) : "r"(a) : "memory");
}
__device__ __forceinline__ void sts128(uint32_t a, const uint32_t* v) {
  asm volatile("st.shared.v4.u32 [%0], {%1, %2, %3, %4};" ::"r"(a), "r"(v[0]), "r"(v[1]), "r"(v[2]), "r"(v[3]) : "memory");
}
__device__ __forceinline__ void sts32(uint32_t a, uint32_t v) {
  asm volatile("st.shared.u32 [%0], %1;" ::"r"(a), "r"(v) : "memory");
}
__device__ __forceinline__ void wait_until(uint32_t t0, uint32_t at) {
  asm volatile(
      "{\n.reg .pred p;\n.reg .s32 r;\n"
      "SPIN:\n"
      "mov.u32 r, %%clock;\n"
      "sub.s32 r, %0, r;\n"
      "setp.gt.s32 p, r, 0;\n"
      "shr.s32 r, r, %1;\n"
      "@p nanosleep.u32 r;\n"
      "@p bra.uni SPIN;\n}\n"
      ::"r"(t0 + at), "n"(NSH) : "memory");
}
__device__ __forceinline__ void wait_exact(uint32_t t0, uint32_t at) {
  if (!THR) return wait_until(t0, at);
  asm volatile(
      "{\n.reg .pred p, q;\n.reg .s32 r;\n"
      "SPIN:\n"
      "mov.u32 r, %%clock;\n"
      "sub.s32 r, %0, r;\n"
      "setp.gt.s32 p, r, 0;\n"
      "setp.gt.s32 q, r, %1;\n"
      "@q nanosleep.u32 %2;\n"
      "@p bra.uni SPIN;\n}\n"
      ::"r"(t0 + at), "n"(THR), "n"(THS) : "memory");
}
__device__ __forceinline__ void spin_until(uint32_t t0, uint32_t at) {
  while ((int)((uint32_t)clock() - t0) < (int)at) {}
}
__device__ __forceinline__ void wait_count(const unsigned int* f, uint32_t& c) {
  asm volatile(
      "{\n.reg .pred p;\n.reg .u32 v;\n"
      "SPIN:\n"
      "ld.acquire.gpu.global.u32 v, [%1];\n"
      "add.u32 %0, %0, 16;\n"
      "setp.lt.u32 p, %0, 0x100000;\n"
      "setp.lt.and.u32 p, v, 64, p;\n"
      "@p nanosleep.u32 100;\n"
      "@p bra.uni SPIN;\n}\n"
      : "+r"(c) : "l"(f) : "memory");
}
template <int E>
__device__ __forceinline__ void ld_lut(uint32_t* v, const __nv_bfloat16* p) {
  asm volatile("ld.global.nc.u32 %0, [%1+%2];" : "=r"(v[E]) : "l"(p), "n"(((E & 3) * N_ + 8 * (E >> 2)) * 2));
  if constexpr (E < 7) ld_lut<E + 1>(v, p);
}
template <int OFF>
__device__ __forceinline__ void ld_codes4(uint32_t* w, const int* p) {
  asm volatile("ld.global.nc.L1::no_allocate.v4.u32 {%0, %1, %2, %3}, [%4+%5];" : "=r"(w[0]), "=r"(w[1]), "=r"(w[2]), "=r"(w[3]) : "l"(p), "n"(OFF));
}
__device__ __forceinline__ void ld_codes(uint32_t* w, const int* p) {
  ld_codes4<0>(w, p);
  ld_codes4<N_ * 4>(w + 4, p);
  ld_codes4<N_ * 32>(w + 8, p);
  ld_codes4<N_ * 36>(w + 12, p);
}
__device__ __forceinline__ void prefetch_map(const CUtensorMap* map) {
  asm volatile("prefetch.tensormap [%0];" ::"l"((uint64_t)map) : "memory");
}
template <int OFF>
__device__ __forceinline__ void ld_words(uint32_t* w, const uint8_t* p) {
  asm volatile("ld.relaxed.gpu.global.v4.u32 {%0, %1, %2, %3}, [%4+%5];" : "=r"(w[0]), "=r"(w[1]), "=r"(w[2]), "=r"(w[3]) : "l"(p), "n"(OFF) : "memory");
}
template <int OFF>
__device__ __forceinline__ void st_words(uint8_t* p, const uint32_t* w) {
  asm volatile("st.relaxed.gpu.global.v4.u32 [%0+%5], {%1, %2, %3, %4};" ::"l"(p), "r"(w[0]), "r"(w[1]), "r"(w[2]), "r"(w[3]), "n"(OFF) : "memory");
}

#define DBGR(i, j)
#define DBG(i)

__device__ __forceinline__ uint32_t word_key(uint32_t odd) { return 0xcdf00000u + (odd << 19); }
__device__ __forceinline__ uint32_t make_word(uint32_t c0, uint32_t c1, uint32_t c2, uint32_t c3, uint32_t key) {
  uint32_t p01, p23, n, w;
  asm("mad.lo.u32 %0, %1, 16, %2;" : "=r"(p01) : "r"(c1), "r"(c0));
  asm("mad.lo.u32 %0, %1, 16, %2;" : "=r"(p23) : "r"(c3), "r"(c2));
  asm("mad.lo.u32 %0, %1, 256, %2;" : "=r"(n) : "r"(p23), "r"(p01));
  asm("mad.lo.u32 %0, %1, 0x7fff, %2;" : "=r"(w) : "r"((n & 0x8888u) | key), "r"(n));
  return w;
}
struct Planes { uint32_t v[4][4]; };
__device__ __forceinline__ void lookup4(const Planes& pl, int c, uint32_t s, uint32_t sc, uint32_t& o0, uint32_t& o1) {
  uint32_t s2;
  asm("{\n.reg .b16 l, h;\n.reg .b32 t;\nmov.b32 {l, h}, %1;\nmov.b32 t, {h, h};\nmul.rn.f16x2 %0, t, %2;\n}\n" : "=r"(s2) : "r"(s), "r"(sc));
  const uint32_t lo = prmt(prmt(pl.v[0][2 * c], pl.v[1][2 * c], s), prmt(pl.v[2][2 * c], pl.v[3][2 * c], s), s2);
  const uint32_t hi = prmt(prmt(pl.v[0][2 * c + 1], pl.v[1][2 * c + 1], s), prmt(pl.v[2][2 * c + 1], pl.v[3][2 * c + 1], s), s2);
  o0 = prmt(lo, hi, 0x5140);
  o1 = prmt(lo, hi, 0x7362);
}
__device__ __forceinline__ void store_planes(uint32_t dst, const uint32_t* lv) {
#pragma unroll
  for (int h = 0; h < 2; h++) {
    uint32_t qp[4];
#pragma unroll
    for (int c = 0; c < 2; c++) {
      const uint32_t a = prmt(lv[4 * c], lv[4 * c + 1], h ? 0x7362 : 0x5140), b = prmt(lv[4 * c + 2], lv[4 * c + 3], h ? 0x7362 : 0x5140);
      qp[2 * c] = prmt(a, b, 0x5410);
      qp[2 * c + 1] = prmt(a, b, 0x7632);
    }
    sts128(dst + 64 * h, qp);
  }
}
__device__ __forceinline__ bool words_ok(const uint32_t* P, uint32_t tag) {
  if (W16) return (P[0] & P[4] & tag) != 0;
  return (P[0] & P[1] & P[2] & P[3] & P[4] & P[5] & P[6] & P[7] & tag) != 0;
}
template <int NJ>
__device__ __forceinline__ void stage_part(const float* a, uint32_t sts) {
#pragma unroll
  for (int j = 0; j < NJ; j++)
    stmatrix_x4_t(sts + 16 * j * 128, pack_bf16(a[8 * j], a[8 * j + 1]), pack_bf16(a[8 * j + 2], a[8 * j + 3]),
                  pack_bf16(a[8 * j + 4], a[8 * j + 5]), pack_bf16(a[8 * j + 6], a[8 * j + 7]));
}

template <int OFF>
__device__ __forceinline__ uint32_t lut_at(uint32_t tab, uint32_t c) {
  uint32_t v;
  asm volatile("ld.shared.u16 %0, [%1+%2];" : "=r"(v) : "r"(tab + 40 * c), "n"(OFF));
  return v;
}
template <int J>
__device__ __forceinline__ void convert_col(const uint32_t (*v)[4], uint32_t tab, uint8_t* dst) {
  uint32_t o[4];
#pragma unroll
  for (int i = 0; i < 4; i++) {
    const uint32_t a = lut_at<2 * J>(tab, v[2 * i][J]), b = lut_at<2 * J>(tab, v[2 * i + 1][J]);
    asm("mad.lo.u32 %0, %1, 65536, %2;" : "=r"(o[i]) : "r"(b), "r"(a));
  }
  st_words<2048 * J>(dst, o);
}

template <int J>
__device__ __forceinline__ void convert_shfl(const uint32_t (*v)[4], uint32_t e, uint8_t* dst) {
  uint32_t o[4];
#pragma unroll
  for (int i = 0; i < 4; i++) {
    uint32_t a, b;
    asm volatile("shfl.sync.idx.b32 %0, %1, %2, 0x101f, 0xffffffff;" : "=r"(a) : "r"(e), "r"(v[2 * i][J]));
    asm volatile("shfl.sync.idx.b32 %0, %1, %2, 0x101f, 0xffffffff;" : "=r"(b) : "r"(e), "r"(v[2 * i + 1][J]));
    o[i] = prmt(a, b, J & 1 ? 0x7632 : 0x5410);
  }
  st_words<2048 * J>(dst, o);
}

struct Maps { CUtensorMap m[NMAPS]; uint64_t desc[6]; const __nv_bfloat16* lut; uint64_t pad; uint32_t tiles[66], jobs[396]; };
struct Tab { uint32_t tiles[66], jobs[396]; };
constexpr int imin(int a, int b) { return a < b ? a : b; }
constexpr Tab make_tab() {
  Tab m{};
  for (int t = 0; t < 66; t++) {
    const int u = t - 32, g = t < 32 ? t & 7 : 1 + u % 7, j = t < 32 ? t >> 3 : 4 + u / 7;
    int cl = t >= 60 ? (int)((0x413B3F394035ull >> (8 * (t - 60))) & 0xff) : g == GB ? 48 + 2 * j : g ? 6 * j + g - 1 - (g > GB) : imin(49 + 6 * j, 87 - 12 * j);
    if (GMAP == 0) cl = (t + 4) % 66;
    const int yi = cl / 6, fb = 2 * (cl % 6);
    const int fa = cl < 48 ? fb : 12 + 2 * (cl & 1), ta = cl < 48 ? TA * yi : imin(TC * ((cl - 48) >> 1), M_ - TC);
    m.tiles[t >= 62 ? t & 3 : t + 4] = fa | fb << 4 | ta << 5 | (TD * yi - (TB - TD) * imin(8 - yi, 0)) << 13;
  }
  int third[396] = {}, t2[396] = {}, by[896] = {}, nt = 0, na = 0;
  for (int i = 0; i < 396; i++) t2[i] = 1;
  for (int b = 0, k = 0; b < 132; b++) {
    if ((m.tiles[b / 2] & 15) < 12) continue;
    third[3 * b] = (k / 2 + 1) * NBC / 36 != (k / 2) * NBC / 36;
    if (third[3 * b] && (nt / 2 + 1) * NTB / NBC != (nt / 2) * NTB / NBC) t2[3 * b] = 0;
    nt += third[3 * b];
    k++;
  }
  const int need = 104 - nt;
  for (int b = 0, k = 0; b < 132; b++) {
    if ((m.tiles[b / 2] & 15) >= 12) continue;
    if (REV & 4 ? na < need : (na / 2 + 1) * need / 96 != (na / 2) * need / 96) {
      third[3 * b] = 1;
      if (k < 12 - NTB) t2[3 * b] = 0;
      k++;
    }
    na++;
  }
  int u = 920, l = 0;
  for (int pass = 0; pass < 2; pass++)
    for (int ii = 0; ii < 396; ii++) {
      const int i = (REV >> pass) & 1 ? 395 - ii : ii;
      if (BF1 ? ((m.tiles[i / 6] & 15) >= 12) == pass : pass) continue;
      m.jobs[i] = third[i] ? u++ : 1024;
      by[third[i] ? m.jobs[i] - 128 : 396 + U0(i / 3, i % 3)] = i + 1;
    }
  for (int k = 0; k < 896; k++) {
    const int i = by[k] - 1;
    if (i < 0) continue;
    if (t2[i]) m.jobs[i] |= l << 11 | imin(LCAP, LT0 + l * LTS) / 8 << 20, l++;
    else m.jobs[i] |= 384 << 11;
  }
  if (l != 384 || u != 1024) m.jobs[400] = 0;
  return m;
}

#define TILES() \
  const int fta = (te & 15) + rank, ftb = ((te >> 4) & 15) + rank, toka = (te >> 5) & 0x7f8, tokb = (te >> 13) & 0x7f8; \
  const bool big = fta < 12; \
  (void)toka; (void)big; (void)tokb; (void)ftb
__global__ void __cluster_dims__(2, 1, 1) __launch_bounds__(NTHREADS, 1)
fused_kernel(unsigned int* __restrict__ count, const __nv_bfloat16* __restrict__ lut, uint8_t* __restrict__ gp,
             const int* __restrict__ qw, const uint8_t* __restrict__ xg, uint64_t desc1, const __grid_constant__ Maps maps) {
  extern __shared__ __align__(1024) uint8_t smem_gen[];
  const uint32_t t0 = clock() + TOF;
  const int tid = threadIdx.x;
  uint32_t cf[16];
  const int* src = qw + (((tid >> 8) * BK + 32 + (tid & 48) + ((tid >> 1) & 6)) * N_ + (blockIdx.x & 127) * 16 + (tid & 3) * 4);
  uint32_t ep0 = 0;
  if ((tid >> 6) == 2) {
    if (EPW) asm volatile("ld.relaxed.gpu.global.u32 %0, [%1];" : "=r"(ep0) : "l"(count) : "memory");
    ld_codes(cf, src);
  }
  const uint32_t te = maps.tiles[blockIdx.x >> 1];
  const int rank = blockIdx.x & 1;
  uint32_t sl;
  asm("mul.lo.u32 %0, %1, 0x1000000;" : "=r"(sl) : "r"(rank));
  sl += SB;
  auto bar = [&](int i) { return sl + OFF_BAR + 8 * i; };
  const int w12 = __shfl_sync(0xffffffffu, tid >> 5, 0);
  const int wg = w12 >> 2;
  const int warp = w12 & 3;
  const int lane = tid & 31;
  uint32_t bud = 0;
  if (__builtin_expect(wg == 0, 1)) {
    asm volatile("setmaxnreg.dec.sync.aligned.u32 72;");
    if (warp == 0) {
      if (lane == 0) {
#pragma unroll
        for (int i = 0; i < NBARS; i++) mbar_init(bar(i), i >= 4 && i < 8 ? 4 : 1);
        mbar_init(bar(B_LAST), 4);
        mbar_init(bar(B_W), 1);
        mbar_init(bar(B_SK), 128);
        for (int i = 1; i <= NX; i++) mbar_init(bar(B_X * i), 1);
        asm volatile("fence.mbarrier_init.release.cluster;" ::: "memory");
      }
      __syncwarp();
      cluster_arrive_relaxed();
      asm volatile("bar.arrive 4, 128;" ::: "memory");
      DBG(1);
      TILES();
      expect_w(bar(B_DIR), 2 * UNIT_BYTES);
      tma3_w(sl + 3 * STAGE_BYTES, &maps.m[M_D], bar(B_DIR), 0, 0, fta * 4);
      const int ca = TR1 && !big ? (TA - TC) * 128 : 0, cb = TR2 && big ? (TB - TD) * 128 : 0;
      const CUtensorMap *ma = &maps.m[M_XA + (ca ? rank : 0)], *mb = &maps.m[M_XB + (cb ? rank : 0)];
      expect_w(bar(B_FULL), X_BYTES - ca);
      cluster_wait();
      tma_mc_w(sl + rank * (X_BYTES / 2), ma, bar(B_FULL), 0, toka + rank * (TA / 2));
      DBG(2);
      expect_w(bar(B_LAST), SLAB_BYTES);
      if (XPE) {
        wait_until(t0, XP0);
        const uint8_t* a = xg + (((blockIdx.x & 127) * 16 + (lane >> 1)) * (K_ * 2) + (lane & 1) * 64);
        if (XPE & 1) asm volatile("prefetch.global.L2 [%0+128];" ::"l"(a));
        if (XPE & 2) asm volatile("prefetch.global.L2 [%0+256];" ::"l"(a));
        if (XPE & 4) asm volatile("prefetch.global.L2 [%0+384];" ::"l"(a));
      }
      if (!NX) wait_exact(t0, XT0);
#pragma unroll
      for (int n = 1; n <= NX; n++) {
        expect_w(bar(B_FULL + n), SLAB_BYTES);
        expect_w(bar(B_X * n), X_BYTES - ca);
        if ((WF >> n) & 1) {
          wait_exact(t0, n == 1 ? G0 : n == 2 ? G1 : G2);
          bulk_w(sl + (n - 1) * STAGE_BYTES + X_BYTES, gp + (fta * KBLKS + n - 1) * SLAB_BYTES, SLAB_BYTES, bar(B_FULL + n));
        }
        if (n == 3) mbar_wait(bar(B_EMPTY + 3), 0, bud);
        wait_exact(t0, n == 1 ? XT0 : n == 2 ? XT2 : XT3);
        tma_mc_w(sl + n * STAGE_BYTES + rank * (X_BYTES / 2), ma, bar(B_X * n), n * BK, toka + rank * (TA / 2));
        DBG(2 + n);
        if (XPD && n >= XPS) {
          const uint8_t* a = xg + (((blockIdx.x & 127) * 16 + (lane >> 1)) * (K_ * 2) + (lane & 1) * 64 + (n + XPD) * 128);
          asm volatile("prefetch.global.L2 [%0];" ::"l"(a));
        }
        if (!((WF >> n) & 1)) {
          wait_exact(t0, n == 1 ? G0 : n == 2 ? G1 : G2);
          bulk_w(sl + (n - 1) * STAGE_BYTES + X_BYTES, gp + (fta * KBLKS + n - 1) * SLAB_BYTES, SLAB_BYTES, bar(B_FULL + n));
        }
      }
#define PT(a)
#pragma unroll 1
      for (int n = NX + 1; n < 2 * KBLKS - 4; n++) {
        const int stage = n & 3;
        const bool first = n < KBLKS;
        const int rows = rank * (first ? TA / 2 : TB / 2);
        if (EXF) expect_w(bar(B_FULL + stage), STAGE_BYTES - (first ? ca : cb));
        mbar_wait(bar(B_EMPTY + stage), ((n - 3) >> 2) & 1, bud);
        PT(pe);
        if (!EXF) expect_w(bar(B_FULL + stage), STAGE_BYTES - (first ? ca : cb));
        tma_mc_w(sl + stage * STAGE_BYTES + rows * 128, first ? ma : mb, bar(B_FULL + stage),
                 (n & (KBLKS - 1)) * BK, (first ? toka : tokb) + rows);
        PT(px);
        if (XPD && n >= XPS && n < KBLKS - XPD) {
          const uint8_t* a = xg + (((blockIdx.x & 127) * 16 + (lane >> 1)) * (K_ * 2) + (lane & 1) * 64 + (n + XPD) * 128);
          asm volatile("prefetch.global.L2 [%0];" ::"l"(a));
          if (!XPW) asm volatile("prefetch.global.L2 [%0+32];" ::"l"(a));
        }
        if (n <= KBLKS) {
          wait_exact(t0, 48 * prmt((uint32_t)GATES, (uint32_t)(GATES >> 32), min(n + 0x776d, 0x7777)));
          bulk_w(sl + ((n - 1) & 3) * STAGE_BYTES + X_BYTES, gp + (fta * KBLKS + n - 1) * SLAB_BYTES, SLAB_BYTES, bar(B_FULL + (n & 19)));
        }
        if (WP && n == 13) asm volatile("bar.arrive 0, 64;" ::: "memory");
        if (WP) continue;
        if (n == PN) wait_count(count + 32 * (1 + ((lds32(sl + OFF_EPOCH) & 256) ? 48 : 0) + 4 * ftb), bud);
        if (first) continue;
        if (n == KBLKS + 4 || n == KBLKS + 8) asm volatile("bar.sync %0, 64;" ::"r"(n & 8) : "memory");
        tma_w(sl + stage * STAGE_BYTES + TB * 128, &maps.m[W128 ? M_W2 : M_W], bar(B_FULL + stage), (n - KBLKS) * BK, ftb * BF);
        if (!W128) tma_w(sl + stage * STAGE_BYTES + TB * 128 + 8192, &maps.m[M_W], bar(B_FULL + stage), (n - KBLKS) * BK, ftb * BF + 64);
        PT(pw);
      }
      const CUtensorMap *mx = &maps.m[M_XB], *mw = &maps.m[M_W];
      DBG(220);
      expect_w(bar(B_RDY), 16384);
      expect_w(bar(B_W), 16384);
      asm volatile("bar.sync 15, %0;" ::"n"(WP ? 128 : 96) : "memory");
      tma3_w(sl + OFF_STG + 49152, mw, bar(B_W), 0, ftb * BF, 14);
      expect_w(bar(B_FULL), STAGE_BYTES);
      uint32_t xd = sl + rank * 12288, xb = bar(B_FULL), xk = (12 + rank) * BK, xt = tokb, wd = sl + 24576, wb = xb, wf = ftb * BF, wk = 12;
#pragma unroll 1
      for (int i = 0; i < 4; i++) {
        wait_tma_mc_w(bar(B_EMPTY) + 8 * i, i == 3, bud, xd, mx, xb, xk, xt);
        if (i < 2) tma3_w(wd, mw, wb, 0, wf, wk);
        wf = ftb * BF + 64;
        if (i == 0) tma3_w(sl + OFF_STG + 16384, mw, bar(B_RDY), 0, wf, 12);
        if (i < 3) expect_w(bar(B_FULL + 1) + 8 * i, i == 2 ? 49152 - 4 * cb : 24576 - 8192 * i);
        xd += STAGE_BYTES; wd += STAGE_BYTES; xk ^= 2 * BK; wk = 14; wb = bar(B_FULL + 2);
        if (i) xb = bar(B_FULL + 3), xt = tokb + TB / 2, mx = &maps.m[cb ? M_XD : M_XB];
        else xb = bar(B_FULL + 1);
      }
      asm volatile(ELECT "@p red.relaxed.gpu.global.add.u32 [%0], %1;\n}\n" ::"l"(count), "r"(blockIdx.x < 2 * NUM_CTAS - 256 ? 1 : 2) : "memory");
    } else {
      const int p = warp - 1;
      uint32_t ep;
      asm volatile("ld.relaxed.gpu.global.u32 %0, [%1];" : "=r"(ep) : "l"(count) : "memory");
      cluster_arrive_relaxed();
      prefetch_map(&maps.m[p + (TR1 && p == 2 && (te & 15) >= 12 ? rank : 0)]);
      asm volatile("prefetch.global.L2 [%0];" ::"l"(xg + (((blockIdx.x * 16 + p * 8 + (lane >> 2)) & (M_ - 1)) * (K_ * 2) + (lane & 3) * 32)));
      const uint32_t so = OFF_STG + p * UNIT_BYTES;
      const uint32_t ua = sl + so + (lane & 3) * 256 + (((lane >> 2) ^ (2 * (lane & 3))) << 4);
      asm volatile("bar.sync 4, 128;" ::: "memory");
      if (!EPW && p == 2) {
        sts32(sl + OFF_EPOCH, ep);
        asm volatile("bar.arrive 1, 288;" ::: "memory");
      }
      int r = blockIdx.x, u = 128 + U0(r, p);
      const uint32_t jobv = maps.jobs[3 * r + p + (tid >> 10)];
      uint32_t job;
      uint32_t ph = 0, odd;
#pragma unroll 1
      do {
        wait_until(t0, PB ? min(D0 + (u - 128) * PU / 4, PE - (1024 - u) * PB / 4) : D0 + (u - 128) * PU / 4);
        expect_w(bar(B_SLOT + p), UNIT_BYTES);
        tma_w(sl + so, &maps.m[M_Q], bar(B_SLOT + p), ((u ^ UX) & 63) * 32, (u & ~63) + 32);
        DBG(16 + 8 * p + 2 * (r / NUM_CTAS));
        uint8_t* dst = gp + ((((((u ^ UX) & 63) >> 2) * KBLKS + (u >> 6)) * 4 + (u & 3)) * 2048 + (lane >> 2) * 256 + (lane & 3) * 16);
        mbar_wait(bar(B_SLOT + p), ph, bud);
        asm volatile("and.b32 %0, %1, 256;" : "=r"(odd) : "r"(ep));
        DBG(184 + 4 * p + r / NUM_CTAS);
        uint32_t w[4][4];
#pragma unroll
        for (int b = 0; b < 4; b++) {
          uint32_t v[4][4];
          lds128(v[0], ua + b * 2048);
          lds128(v[1], (ua ^ 16) + b * 2048 + 128);
          lds128(v[2], ua + b * 2048 + 1024);
          lds128(v[3], (ua ^ 16) + b * 2048 + 1024 + 128);
#pragma unroll
          for (int j = 0; j < 4; j++) w[j][b] = make_word(v[0][j], v[1][j], v[2][j], v[3][j], word_key(odd));
        }
        st_words<0>(dst, w[0]); st_words<64>(dst, w[1]); st_words<128>(dst, w[2]); st_words<192>(dst, w[3]);
        __syncwarp();
        DBG(17 + 8 * p + 2 * (r / NUM_CTAS));
        ph ^= 1;
        r += NUM_CTAS;
        job = __shfl_sync(0xffffffffu, jobv, 0);
        u = ph ? u + 3 * NUM_CTAS : job & 2047;
      } while (u < 1024);
      const int l = (job >> 11) & 511;
      const int ls = (l * 1366) >> 16, cg = l - 48 * ls;
      unsigned int* cnt = count + (32 + 6 * __shfl_sync(0xffffffffu, odd, 0));
      prefetch_map(&maps.m[M_XB + p]);
      prefetch_map(&maps.m[M_Q2]);
      if (l < 384) {
        uint32_t e[8];
        const __nv_bfloat16* s = maps.lut + ((lane & 15) * N_ + 2048 + cg * 32 + (lane & 16));
        asm volatile("ld.global.nc.v4.u32 {%0, %1, %2, %3}, [%4];" : "=r"(e[0]), "=r"(e[1]), "=r"(e[2]), "=r"(e[3]) : "l"(s));
        asm volatile("ld.global.nc.v4.u32 {%0, %1, %2, %3}, [%4+16];" : "=r"(e[4]), "=r"(e[5]), "=r"(e[6]), "=r"(e[7]) : "l"(s));
        wait_until(t0, (job >> 20) * 8);
        expect_w(bar(B_SLOT + p), 2 * UNIT_BYTES);
        tma3_w(sl + so, &maps.m[M_Q2], bar(B_SLOT + p), 2048 + cg * 32, ls * 16, 0);
        tma3_w(sl + so + 32768, &maps.m[M_Q2], bar(B_SLOT + p), 2048 + cg * 32, ls * 16, 4);
        DBG(22 + 8 * p);
        uint32_t tab = sl + OFF_TAB + p * 1536 + (SHF ? lane * 32 : (lane >> 4) * 644);
        if (SHF) {
          sts128(tab, e);
          sts128(tab + 16, e + 4);
        } else {
#pragma unroll
          for (int i = 0; i < 8; i++) sts32(tab + (lane & 15) * 40 + 4 * i, e[i]);
          __syncwarp();
        }
        uint8_t* dst = gp + (W_OFF + cg * 65536 + ls * 256 + (lane >> 4) * 32768 + (lane & 15) * 16);
        const uint32_t src = sl + so + (lane & 15) * 128 + ((((lane >> 2) & 4) ^ (lane & 7)) << 4);
        mbar_wait(bar(B_SLOT + p), ph, bud);
#pragma unroll 1
        for (int c = 0; c < 64; c += 16, tab += 8, dst += 8192) {
          uint32_t v[8][4];
#pragma unroll
          for (int i = 0; i < 8; i++) lds128(v[i], (src ^ c) + (i & 3) * 2048 + (i >> 2) * 32768);
          if (SHF) {
            asm volatile("ld.shared.v2.u32 {%0, %1}, [%2];" : "=r"(e[0]), "=r"(e[1]) : "r"(tab) : "memory");
            convert_shfl<0>(v, e[0], dst);
            convert_shfl<1>(v, e[0], dst);
            convert_shfl<2>(v, e[1], dst);
            convert_shfl<3>(v, e[1], dst);
          } else {
          convert_col<0>(v, tab, dst);
          convert_col<1>(v, tab, dst);
          convert_col<2>(v, tab, dst);
          convert_col<3>(v, tab, dst);
          }
        }
        __syncwarp();
        DBG(23 + 8 * p);
      }
      arrive_w(bar(B_LAST));
      if (l < 384)
        asm volatile(ELECT "@p fence.proxy.async.global;\n@p red.release.gpu.global.add.u32 [%0], %1;\n}\n"
                     ::"l"(cnt + 32 * ((cg & ~3) + min(ls >> 1, 2))), "r"(ls < 4 ? 8 : 4) : "memory");
      cluster_wait();
      TILES();
      const int q = WP ? (RM >> (p + p)) & 3 : p;
      prefetch_map(&maps.m[M_W - q]);
      prefetch_map(&maps.m[M_W2]);
      if (q > 0) {
        asm volatile("bar.sync %0, 160;" ::"r"(12 + q) : "memory");
        if (FEN) asm volatile("fence.proxy.async.shared::cta;" ::: "memory");
        uint32_t t1 = clock();
#pragma unroll 1
        for (int i = 0; i < TA; i += OB, t1 += PC * OB / 32) {
          wait_until(t1, 0);
          const int rr = min(i ^ 128, (big ? TA : TC) - OB);
          if (i == 128) {
            bulk_wait_read();
            asm volatile("bar.arrive 15, %0;" ::"n"(WP ? 128 : 96) : "memory");
          }
          store_w(&maps.m[M_O32], sl + OFF_STG + (q - 1) * 32768 + rr * 128, fta * BF + 64 * (q - 1), toka + rr);
        }
        bulk_wait_read();
        DBG(227 + q);
        asm volatile("bar.arrive %0, 160;" ::"r"(12 + q) : "memory");
        const uint32_t sg = sl + OFF_STG + (q - 1) * 32768;
        const int c0 = 2048 + ftb * BF + 64 * (q - 1);
        uint32_t ids = q == 1 ? 0x0d126 : 0x8e437;
        const CUtensorMap* mo = &maps.m[M_O48];
        uint32_t os = sg + 48 * 128, ot = tokb + 48;
#pragma unroll 1
        for (int k = 0; k < 5; k++) {
          asm volatile("bar.sync %0, 160;\nfence.proxy.async.shared::cta;\n"
                       ELECT "@p cp.async.bulk.tensor.2d.global.shared::cta.bulk_group [%1, {%3, %4}], [%2];\n}\n"
                       "cp.async.bulk.commit_group;"
                       ::"r"((ids & 15) | ((os + ot + k + (uint32_t)((uint64_t)mo >> 32)) & (bud >> 31))), "l"((uint64_t)mo), "r"(os), "r"(c0), "r"(ot) : "memory");
          const int r = k ? 64 + 32 * k : 0;
          ids >>= 4; os = sg + r * 128; ot = tokb + r;
          if (k == 1 || (k == 3 && big)) mo--;
        }
        bulk_wait_read();
      } else {
        if (blockIdx.x < 48) count[32 * (50 + blockIdx.x) - (cnt - count)] = 0;
        if (WP) {
          asm volatile("bar.sync 0, 64;" ::: "memory");
#pragma unroll 1
          for (int n = 0; n < KBLKS - 4; n++) {
            if ((n & 3) == 0) wait_count(cnt + 32 * 4 * ftb + 8 * n, bud);
            if (n == 8) asm volatile("bar.arrive 15, 128;" ::: "memory");
            mbar_wait(bar(B_EMPTY + (n & 3)), ((n + 13) >> 2) & 1, bud);
            tma_w(sl + (n & 3) * STAGE_BYTES + TB * 128, &maps.m[W128 ? M_W2 : M_W], bar(B_FULL + (n & 3)), n * BK, ftb * BF);
            if (!W128) tma_w(sl + (n & 3) * STAGE_BYTES + TB * 128 + 8192, &maps.m[M_W], bar(B_FULL + (n & 3)), n * BK, ftb * BF + 64);
          }
        } else {
#pragma unroll 1
        for (int i = 1; i < 3; i++) {
          wait_count(cnt + 32 * (4 * ftb + i), bud);
          asm volatile("bar.arrive %0, 64;" ::"r"(8 * i - 8) : "memory");
        }
        }
      }
    }
    asm volatile("exit;");
  }
  const int cw = wg - 1;
  TILES();
  cluster_arrive_relaxed();
  if (warp >= 2) {
    ld_lut<0>(cf, lut + (fta * BF + 4 * (lane & 3) * N_ + 64 * cw + 32 * (warp & 1) + (lane & 16) + ((lane >> 1) & 6)));
  } else if (cw) {
    spin_until(t0, S1D);
    ld_codes(cf, src);
  } else if (EPW) {
    sts32(sl + OFF_EPOCH, ep0);
    asm volatile("bar.arrive 1, 256;" ::: "memory");
  }
  if (EPW) {
    if (w12 >= 6) asm volatile("bar.sync 1, 256;" ::: "memory");
  } else asm volatile("bar.sync 1, 288;" ::: "memory");
  const uint32_t odd = lds32(sl + OFF_EPOCH) & 256;
  DBG(40 + w12);
  if (warp >= 2) store_planes(sl + OFF_PL + cw * 32768 + (warp & 1) * 1024 + (lane & 28) * 32 + (lane & 3) * 16, cf);
  else {
    uint8_t* dst = gp + (((blockIdx.x & 120) * 2 + cw) * SLAB_BYTES + (blockIdx.x & 7) * 1024 + (tid & 63) * 16);
    const uint32_t tb = sl + OFF_STG + 61440 + cw * 1024;
#pragma unroll
    for (int j = 0; j < 4; j++)
      sts32(tb + (lane & 3) * 256 + j * 64 + (lane & 12) * 4 + ((tid >> 2) & 12), make_word(cf[j], cf[4 + j], cf[8 + j], cf[12 + j], word_key(odd)));
    asm volatile("bar.sync %0, 64;" ::"r"(6 + cw) : "memory");
    lds128(cf, tb + (tid & 63) * 16);
    st_words<0>(dst, cf);
  }
  DBG(52 + w12);
  asm volatile("setmaxnreg.inc.sync.aligned.u32 216;");
  uint32_t rel = (tid & 127) < 2 ? mapa(bar(B_EMPTY), lane) : 0u;
  uint32_t tg = (w12 - 4) * 1024 + lane * 16;
  uint32_t tw = sl + X_BYTES + tg;
  const uint8_t* gt = gp + (tg + fta * KBLKS * SLAB_BYTES);
  uint32_t tag = (1u << 28) - (odd << 19), sc = 0x3c00 + 8 * odd;
  asm volatile("" : "+r"(tw), "+l"(gt), "+r"(rel), "+r"(tag), "+r"(sc));
  Planes pl;
  uint32_t A[16], P[8];
  float acc[TA / 2];
  DBG(64 + cw);
  if (PLF) {
  asm volatile("bar.sync %0, 128;" ::"r"(2 + cw) : "memory");
#pragma unroll
  for (int k = 0; k < 4; k++) lds128(pl.v[k], sl + OFF_PL + cw * 32768 + (tid & 124) * 16 + 16 * k);
  }
  {
    const uint32_t td = sl + 3 * STAGE_BYTES - 8192 + (w12 >> 1) * 4096 + (lane & 3) * 256 + ((((tid >> 3) & 4) ^ (lane >> 4) ^ (2 * (lane & 3))) << 4) + (lane & 12);
    mbar_wait(bar(B_DIR), 0, bud);
    DBG(88 + cw);
#pragma unroll
    for (int k = 0; k < 4; k++) {
      const uint32_t a = (td ^ ((k & 2) << 4)) + (k & 1) * 2048;
      P[2 + (k & 1) + 2 * (k & 2)] = make_word(lds32(a), lds32((a ^ 16) + 128), lds32(a + 1024), lds32((a ^ 16) + 1152), word_key(odd));
    }
  }
  if (!PLF) {
  asm volatile("bar.sync %0, 128;" ::"r"(2 + cw) : "memory");
#pragma unroll
  for (int k = 0; k < 4; k++) lds128(pl.v[k], sl + OFF_PL + cw * 32768 + (tid & 124) * 16 + 16 * k);
  }
  if (!NX) mbar_wait(bar(B_FULL), 0, bud);
  DBG(66 + cw);
#define CNT(i)
  auto rest = [&](auto ty) {
  constexpr bool big = decltype(ty)::v;
  auto tile1 = [&](auto nh) {
    uint32_t fb = bar(B_LAST) - 128 * cw, fm = 0x98 + 128 * cw;
    asm volatile("" : "+r"(fb), "+r"(fm));
    uint64_t d = desc1;
    uint32_t m = 128, pa = 0;
#pragma unroll 1
    do {
      m += 8;
      uint32_t fa;
      asm volatile("lop3.b32 %0, %1, %2, %3, 0x6a;" : "=r"(fa) : "r"(m), "r"(fm), "r"(fb));
      const uint32_t o = m & 24, par = PAR ? m >> 5 : (m >> 5) & 1;
      bool ok;
#pragma unroll
      for (int b = 0; b < 4; b++) {
        if (b == 1 && !ok) mbar_wait(fa, par, bud);
        if (b == 2) {
#pragma unroll 1
          while (__builtin_expect(!__all_sync(0xffffffffu, words_ok(P, tag)), 0)) {
            if ((bud += 16) >= 0x100000) break;
            asm volatile("{\n.reg .b64 a, l, h;\n.reg .b128 t, u;\nmad.wide.u32 a, %8, 1024, %9;\n"
                         "ld.relaxed.gpu.global.b128 t, [a+-139264];\nld.relaxed.gpu.global.b128 u, [a+-138752];\n"
                         "mov.b128 {l, h}, t;\nmov.b64 {%0, %1}, l;\nmov.b64 {%2, %3}, h;\n"
                         "mov.b128 {l, h}, u;\nmov.b64 {%4, %5}, l;\nmov.b64 {%6, %7}, h;\n}\n"
                         : "=r"(P[0]), "=r"(P[1]), "=r"(P[2]), "=r"(P[3]), "=r"(P[4]), "=r"(P[5]), "=r"(P[6]), "=r"(P[7]) : "r"(m), "l"(gt) : "memory");
          }
        }
        CNT(2 * b);
        lookup4(pl, 0, P[b ^ 2], sc, A[4 * b], A[4 * b + 2]);
        lookup4(pl, 1, P[4 + (b ^ 2)], sc, A[4 * b + 1], A[4 * b + 3]);
        if (b == 1) {
          lds128(P, tw + pa);
          lds128(P + 4, tw + pa + 512);
        }
        if (b == 1) asm volatile("mul.lo.u32 %0, %1, %2;" : "=r"(pa) : "r"(o), "n"(STAGE_BYTES / 8));
        if (((WD >> (4 * b)) & 3) == 1) wgmma_wait<1>();
        if (((WD >> (4 * b)) & 3) == 2) wgmma_wait<2>();
        if (b == RB) mbar_arrive_remote_if(rel + (o ^ 16), rel);
        if (b == 0) ok = mbar_test(fa, par);
        if (NX && b == 0 && m < 144 + 8 * NX) {
          uint32_t xa;
          asm volatile("mad.lo.u32 %0, %1, %2, %3;" : "=r"(xa) : "r"(m), "n"(B_X), "r"(bar(B_FULL) - 136 * B_X));
          mbar_wait(xa, 0, bud);
        }
        CNT(2 * b + 1);
        wgmma_fence();
        if (b) wgmma_rl<decltype(nh)::v>(acc, A + 4 * b, d + 2 * b + 2);
        else wgmma_rp<decltype(nh)::v>(acc, A, d + 2, m > 136);
        wgmma_commit();
      }
      asm volatile("mov.b64 %0, {%1, %2};" : "=l"(d) : "r"(UD - 2 + (pa >> 4)), "r"((uint32_t)(d >> 32)));
    } while (m < 256);
  };
  tile1(IC<big ? TA : TC>());
  if (cw != 1) mbar_arrive(bar(B_SK));
  const uint32_t stg = sl + OFF_STG + cw * 32768;
  const uint32_t so8 = stg + ((lane & 7) + ((lane >> 4) << 3)) * 128 + (((2 * warp + ((lane >> 3) & 1)) ^ (lane & 7)) << 4);
  DBG(212 + cw);
  mbar_wait(bar(B_FULL), 0, bud);
  DBG(214 + cw);
  DBG(216 + cw);
  const uint64_t ub = maps.desc[3 * big], ua = ub + (TB * 8 + cw * 512);
  const uint64_t vb = maps.desc[3 * big + 1], va = vb + (TB * 8 + cw * 512), uc = maps.desc[3 * big + 2];
  wgmma_wait<0>();
  mbar_arrive_remote_if(rel + 24, rel);
  fence_regs(acc);
  DBGR(0, 68 + cw);
#define PKT(i)
  auto start2 = [&](auto nt) {
    uint32_t o[64];
#pragma unroll
    for (int k = 0; k < 48; k++) o[k] = pack_bf16(acc[2 * k], acc[2 * k + 1]);
#pragma unroll
    for (int k = 0; k < 48; k++) asm volatile("" : "+r"(o[k]) :: "memory");
    DBG(92 + cw);
    PKT(0);
    wgmma_fence();
#pragma unroll
    for (int b = 0; b < 4 * NP; b++) {
      const int so = (b >> 2) * (STAGE_BYTES / 16) + 2 * (b & 3);
      if (b && !(b & 3)) mbar_wait(bar(B_FULL + (b >> 2)), 0, bud);
      wgmma_ss<decltype(nt)::v>(acc, ua + so, ub + so, b != 0);
      if ((b & 3) == 3 || (b && !(b & 3))) wgmma_commit();
      if (b == 0) {
#pragma unroll
        for (int k = 48; k < 64; k++) o[k] = pack_bf16(acc[2 * k], acc[2 * k + 1]);
      }
      if (b && !(b & 3)) {
        wgmma_wait<1>();
        mbar_arrive_remote_if(rel + 2 * b - 8, rel);
      }
#pragma unroll
      for (int j = 0; j < 16; j++)
        if (((SMK >> (4 * j)) & 15) == b) stmatrix_x4_t(so8 + (j ^ SJ) * 2048, o[4 * (j ^ SJ)], o[4 * (j ^ SJ) + 1], o[4 * (j ^ SJ) + 2], o[4 * (j ^ SJ) + 3]);
      PKT(b + 1);
    }
  };
  start2(IC<big ? TD : TB>());
  if (!FEN) asm volatile("fence.proxy.async.shared::cta;" ::: "memory");
  asm volatile("bar.arrive %0, 160;" ::"r"(13 + cw) : "memory");
  cluster_wait();
  DBG(70 + cw);
  uint32_t W[64];
  const uint32_t wa = sl + (warp * 16 + (lane & 15)) * 128 + (((lane >> 4) ^ (lane & 7)) << 4);
  const uint32_t w0 = wa + (cw ? OFF_STG + 16384 : 24576), w2 = wa + (cw ? STAGE_BYTES + 24576 : OFF_STG + 49152);
  auto tile2 = [&](auto nt) {
    auto step = [&](int n, bool last) {
      const uint32_t so = (n & 3) * (STAGE_BYTES / 16);
      mbar_wait_fast(bar(B_FULL) + 8 * (n & 3), (n >> 2) & 1, bud);
      if (last && EW == 0) mbar_wait(bar(B_W), 0, bud);
      wgmma_fence();
      wgmma_ss<decltype(nt)::v>(acc, va + so, vb + so, 1);
      wgmma_commit();
      if (last) {
        if (EW == 1) mbar_wait(bar(B_W), 0, bud);
#pragma unroll
        for (int b = 8; b < U0A; b++) {
          if (PEEL) ldmatrix_x4_if(W + 4 * b, (w2 ^ ((b & 3) << 5)) + ((b >> 2) & 1) * 8192, cw);
          else ldmatrix_x4(W + 4 * b, (w2 ^ ((b & 3) << 5)) + ((b >> 2) & 1) * 8192);
        }
      }
      wgmma_wait<1>();
      mbar_arrive_remote_if(rel + 8 * ((n - 1) & 3), rel);
#pragma unroll
      for (int b = 1; b < 4; b++) wgmma_ss<decltype(nt)::v>(acc, va + so + 2 * b, vb + so + 2 * b, 1);
      wgmma_commit();
    };
#pragma unroll 1
    for (int n = NP; n < KBLKS - 4; n++) step(n, n == KBLKS - 5 + 8 * cw);
  };
  tile2(IC<big ? TD : TB>());
  float c2[TB / 2];
  DBGR(1, 72 + cw);
  auto ldw = [&](int b) { ldmatrix_x4(W + 4 * b, ((b & 8 ? w2 : w0) ^ ((b & 3) << 5)) + ((b >> 2) & 1) * 8192); };
  const uint32_t b2 = bar(B_FULL + 1 + cw);
  mbar_wait(bar(cw ? B_RDY : B_FULL), 1, bud);
  if (cw) DBG(226);
#pragma unroll
  for (int b = 0; b < PF; b++) {
    ldw(b);
  }
  bool ok = false;
  wgmma_wait<0>();
  mbar_arrive_remote_if(rel + 24, rel);
  if (PKI == -2) ok = mbar_test(b2, 1);
  if (cw) {
    mbar_wait(b2, 1, bud);
    DBG(227);
#pragma unroll
    for (int b = 8; b < UA; b++) ldw(b);
  }
#pragma unroll
  for (int k = 0; k < TB / 2; k++) asm volatile("mov.b32 %0, %1;" : "=f"(c2[k]) : "f"(acc[k]) : "memory");
#pragma unroll
  for (int h = 0; h < 2 - T3; h++) {
    constexpr int L = 48;
    if (h) mbar_wait(bar(B_FULL + 3), 1, bud);
    if (h || cw) asm volatile("bar.sync %0, 256;" ::"r"(9 + 2 * h + cw) : "memory");
    DBGR(2 + 3 * h, 74 + 6 * h + cw);
    if (h == 0 && PKI == -1) ok = mbar_test(b2, 1);
    auto part = [&](auto nn) {
#pragma unroll
      for (int i = 0; i < 16; i++) {
        if (h ? i >= QD1 && i <= QN1 : i >= QD0 && i <= QN0) {
          if (h) wgmma_wait<QD1 - 1>(); else wgmma_wait<QD0 - 1>();
        }
        if (i == 0 || (h == 0 && ((FM0 >> i) & 1))) wgmma_fence();
        const int off = ((2 * h + (i >> 3)) * STAGE_BYTES + ((i >> 2) & 1) * 12288 + L * 128) / 16 + 2 * (i & 3);
        if constexpr (decltype(nn)::v == TB / 2 - L) wgmma_rl<decltype(nn)::v>(c2 + 48 * h + L / 2, W + 4 * i, uc + off);
        else wgmma_rs<decltype(nn)::v>(c2 + 48 * h + L / 2, W + 4 * i, UD + off, 1);
        if (h == 0 && i < IX) wgmma_rl<L>(c2, W + 4 * i, uc + off - L * 8);
        if (i < (h ? QN1 : QN0) || (!h && i == NA)) wgmma_commit();
        if (h == 0) {
          constexpr int J0 = U0A < UA ? U0A : UA;
#pragma unroll
          for (int e = 0; e < LPS; e++) {
            const int j = (i - LD0) * LPS + J0 + e;
            if (j >= J0 && j < UA) ldmatrix_x4_if(W + 4 * j, (w2 ^ ((j & 3) << 5)) + ((j >> 2) & 1) * 8192, cw);
            else if (j >= J0 && j < U0A) ldmatrix_x4_if(W + 4 * j, (w2 ^ ((j & 3) << 5)) + ((j >> 2) & 1) * 8192, cw ^ 1);
            else if (j >= J0 && j < 16) ldw(j);
          }
          if (i == PKI) ok = mbar_test(b2, 1);
          if (i == WI && !ok) mbar_wait(b2, 1, bud);
        }
      }
      wgmma_commit();
    };
    if (h && big) part(IC<TD - TB / 2 - L>()); else part(IC<TB / 2 - L>());
    const int k0 = h ? K0 : K00 + IX;
    if (h) wgmma_fence();
#pragma unroll
    for (int i = h ? 0 : IX; i < 16; i++) {
      const int off = ((2 * h + (i >> 3)) * STAGE_BYTES + ((i >> 2) & 1) * 12288) / 16 + 2 * (i & 3);
      wgmma_rl<L>(c2 + 48 * h, W + 4 * i, uc + off);
      if (i == k0 - 1) {
        wgmma_commit();
        if (!h) asm volatile("bar.sync %0, 160;" ::"r"(13 + cw) : "memory");
        if (!h) {
          wgmma_wait<2>();
          asm volatile("bar.arrive %0, 256;" ::"r"(10 + cw) : "memory");
        }
        wgmma_wait<1>();
#pragma unroll
        for (int k = L / 2; k < 48; k++) asm volatile("" : "+f"(c2[48 * h + k]) :: "memory");
        if (h == TCH) DBGR(8, 218 + cw);
      }
      const int j = i - k0 + 1 + L / 16;
      if (i >= k0 - 1 && j < 6) stage_part<1>(c2 + 48 * h + 8 * j, so8 + 16 * 128 * (6 * h + j));
      if (j == 5) asm volatile("bar.arrive %0, 160;" ::"r"(h ? 1 + 3 * cw : 6 + cw) : "memory");
    }
    wgmma_commit();
    if (h) asm volatile("{\n.reg .pred p;\nsetp.eq.u32 p, %0, 0;\n@p bar.arrive 12, 256;\n}\n" ::"r"(cw) : "memory");
    if (h == TCH) DBGR(9, 230 + cw);
    wgmma_wait<0>();
#pragma unroll
    for (int k = 0; k < L / 2; k++) asm volatile("" : "+f"(c2[48 * h + k]) :: "memory");
    DBGR(3 + 3 * h, 76 + 6 * h + cw);
    stage_part<L / 16>(c2 + 48 * h, so8 + 96 * 128 * h);
    asm volatile("bar.arrive %0, 160;" ::"r"(h ? 8 * cw : 2 + cw) : "memory");
    DBGR(4 + 3 * h, 78 + 6 * h + cw);
  }
  if (T3) {
    mbar_wait(bar(B_FULL + 3), 1, bud);
    asm volatile("bar.sync %0, 256;" ::"r"(11 + cw) : "memory");
    DBGR(5, 80 + cw);
    auto part = [&](auto nn, auto pp) {
      constexpr int p = decltype(pp)::v;
      constexpr int kk = p == 2 ? K4 : K3;
      float* c = c2 + 48 + 16 * p;
      wgmma_fence();
#pragma unroll
      for (int i = 0; i < 16; i++) {
        if (p == 0 && i >= QD3 && i <= QN3) wgmma_wait<QD3 - 1>();
        const int off = ((2 + (i >> 3)) * STAGE_BYTES + ((i >> 2) & 1) * 12288 + 32 * p * 128) / 16 + 2 * (i & 3);
        if constexpr (p == 2 && decltype(nn)::v == R24) wgmma_rs<decltype(nn)::v>(c, W + 4 * i, UD + off, 1);
        else wgmma_rl<decltype(nn)::v>(c, W + 4 * i, uc + off);
        if (p == 0 && i < QN3) wgmma_commit();
        if (p == 2 && i == HI) asm volatile("{\n.reg .pred p;\nsetp.eq.u32 p, %0, 0;\n@p bar.arrive 12, 256;\n}\n" ::"r"(cw) : "memory");
        if (p && i == kk - 1) {
          wgmma_commit();
          wgmma_wait<1>();
#pragma unroll
          for (int k = -16; k < 0; k++) asm volatile("" : "+f"(c[k]) :: "memory");
          if (TCH && p == TCH) DBGR(8, 218 + cw);
        }
        const int j = i - kk + 1;
        if (p && (j == 0 || j == 1)) stage_part<1>(c - 16 + 8 * j, so8 + (64 + 32 * p + 16 * j) * 128);
        if (p && j == 1 + AD) asm volatile("bar.arrive %0, 160;" ::"r"(p == 1 ? 1 + 3 * cw : 13 + cw) : "memory");
      }
      wgmma_commit();
    };
    part(IC<32>(), IC<0>());
    part(IC<32>(), IC<1>());
    part(IC<big ? 24 : 32>(), IC<2>());
    if (HI == 16) asm volatile("{\n.reg .pred p;\nsetp.eq.u32 p, %0, 0;\n@p bar.arrive 12, 256;\n}\n" ::"r"(cw) : "memory");
    if (TCH) DBGR(9, 230 + cw);
    wgmma_wait<0>();
#pragma unroll
    for (int k = 80; k < 96; k++) asm volatile("" : "+f"(c2[k]) :: "memory");
    DBGR(6, 82 + cw);
    stage_part<2>(c2 + 80, so8 + 160 * 128);
    asm volatile("bar.arrive %0, 160;" ::"r"(8 * cw) : "memory");
    DBGR(7, 84 + cw);
  }
  if (big && PADN) {
    asm volatile("{\n.reg .pred p;\nsetp.ge.s32 p, %0, 0;\n@p exit;\n}\n" ::"r"(bud) : "memory");
#pragma unroll
    for (int i = 0; i < PADN; i++) asm volatile("membar.cta;" ::: "memory");
  }
  };
  if (!big) rest(IC<0>()); else rest(IC<1>());
}

typedef CUresult (*EncodeFn)(CUtensorMap*, CUtensorMapDataType, cuuint32_t, void*, const cuuint64_t*, const cuuint64_t*,
                             const cuuint32_t*, const cuuint32_t*, CUtensorMapInterleave, CUtensorMapSwizzle,
                             CUtensorMapL2promotion, CUtensorMapFloatOOBfill);

}

extern "C" void kernel_launch(void* const* d_in, const int* in_sizes, int n_in, void* d_out, int out_size) {
  const __nv_bfloat16* x = (const __nv_bfloat16*)d_in[0];
  const int* qw = (const int*)d_in[1];
  const __nv_bfloat16* lut = (const __nv_bfloat16*)d_in[2];

  static EncodeFn enc = nullptr;
  static unsigned int* count = nullptr;
  static uint8_t* gp = nullptr;
  if (!enc) {
    cudaDriverEntryPointQueryResult q;
    void* fn = nullptr;
    cudaGetDriverEntryPoint("cuTensorMapEncodeTiled", &fn, cudaEnableDefault, &q);
    enc = (EncodeFn)fn;
    cudaGetSymbolAddress((void**)&count, g_count);
    cudaGetSymbolAddress((void**)&gp, g_p);
    cudaFuncSetAttribute(fused_kernel, cudaFuncAttributeMaxDynamicSharedMemorySize, SMEM_BYTES);
  }
  Maps maps;
  const cuuint32_t es[3] = {1, 1, 1};
  auto map2 = [&](int i, CUtensorMapDataType t, const void* p, int d0, int d1, int bytes, int b0, int b1, CUtensorMapL2promotion pr) {
    cuuint64_t dims[2] = {(cuuint64_t)d0, (cuuint64_t)d1};
    cuuint64_t strides[1] = {(cuuint64_t)d0 * bytes};
    cuuint32_t box[2] = {(cuuint32_t)b0, (cuuint32_t)b1};
    enc(&maps.m[i], t, 2, (void*)p, dims, strides, box, es, CU_TENSOR_MAP_INTERLEAVE_NONE, CU_TENSOR_MAP_SWIZZLE_128B, pr, CU_TENSOR_MAP_FLOAT_OOB_FILL_NONE);
  };
  map2(M_XA, CU_TENSOR_MAP_DATA_TYPE_BFLOAT16, x, K_, M_, 2, BK, TA / 2, XPROM);
  map2(M_XC, CU_TENSOR_MAP_DATA_TYPE_BFLOAT16, x, K_, M_, 2, BK, TC - TA / 2, XPROM);
  map2(M_XD, CU_TENSOR_MAP_DATA_TYPE_BFLOAT16, x, K_, M_, 2, BK, TD - TB / 2, XPROM);
  map2(M_XB, CU_TENSOR_MAP_DATA_TYPE_BFLOAT16, x, K_, M_, 2, BK, TB / 2, XPROM);
  map2(M_O24, CU_TENSOR_MAP_DATA_TYPE_BFLOAT16, d_out, N_, M_, 2, 64, 24, CU_TENSOR_MAP_L2_PROMOTION_NONE);
  map2(M_O32, CU_TENSOR_MAP_DATA_TYPE_BFLOAT16, d_out, N_, M_, 2, 64, OB, CU_TENSOR_MAP_L2_PROMOTION_NONE);
  map2(M_O48, CU_TENSOR_MAP_DATA_TYPE_BFLOAT16, d_out, N_, M_, 2, 64, 48, CU_TENSOR_MAP_L2_PROMOTION_NONE);
  map2(M_Q, CU_TENSOR_MAP_DATA_TYPE_INT32, qw, N_, K_, 4, 32, BK, QPROM);
  {
    cuuint64_t dims[3] = {BK, (cuuint64_t)N_ - 2048, KBLKS};
    cuuint64_t strides[2] = {(cuuint64_t)K_ * 2, BK * 2};
    cuuint32_t box[3] = {BK, 64, 2};
    enc(&maps.m[M_W], CU_TENSOR_MAP_DATA_TYPE_BFLOAT16, 3, (void*)(gp + W_OFF), dims, strides, box, es, CU_TENSOR_MAP_INTERLEAVE_NONE,
        CU_TENSOR_MAP_SWIZZLE_128B, XPROM, CU_TENSOR_MAP_FLOAT_OOB_FILL_NONE);
  }
  map2(M_W2, CU_TENSOR_MAP_DATA_TYPE_BFLOAT16, gp + W_OFF, K_, N_ - 2048, 2, BK, 128, XPROM);
  {
    cuuint64_t dims[3] = {(cuuint64_t)N_, (cuuint64_t)K_ / 8, 8};
    cuuint64_t strides[2] = {(cuuint64_t)N_ * 32, (cuuint64_t)N_ * 4};
    cuuint32_t box[3] = {32, 16, 4};
    enc(&maps.m[M_Q2], CU_TENSOR_MAP_DATA_TYPE_INT32, 3, (void*)qw, dims, strides, box, es, CU_TENSOR_MAP_INTERLEAVE_NONE,
        CU_TENSOR_MAP_SWIZZLE_128B, QPROM, CU_TENSOR_MAP_FLOAT_OOB_FILL_NONE);
  }
  {
    cuuint64_t dims[3] = {32, (cuuint64_t)K_, (cuuint64_t)N_ / 32};
    cuuint64_t strides[2] = {(cuuint64_t)N_ * 4, 128};
    cuuint32_t box[3] = {32, 32, 4};
    enc(&maps.m[M_D], CU_TENSOR_MAP_DATA_TYPE_INT32, 3, (void*)qw, dims, strides, box, es, CU_TENSOR_MAP_INTERLEAVE_NONE,
        CU_TENSOR_MAP_SWIZZLE_128B, QPROM, CU_TENSOR_MAP_FLOAT_OOB_FILL_NONE);
  }
  for (int i = 0; i < 6; i++) maps.desc[i] = (0x40000040ull << 32) + UD;
  maps.lut = lut;
  maps.pad = 0;
  constexpr Tab tab = make_tab();
  for (int t = 0; t < 66; t++) maps.tiles[t] = tab.tiles[t];
  for (int i = 0; i < 396; i++) maps.jobs[i] = tab.jobs[i];
  fused_kernel<<<NUM_CTAS, NTHREADS, SMEM_BYTES, cudaStreamPerThread>>>(count, lut, gp, qw, (const uint8_t*)x, maps.desc[0] - 2, maps);
}
```
